```python
import torch

def _softmax(x, axis=-1):
    return torch.softmax(x, dim=axis)
def _gelu(x):
    return torch.nn.functional.gelu(x, approximate="tanh")
def _silu(x):
    return torch.nn.functional.silu(x)
def _sigmoid(x):
    return torch.sigmoid(x)
def _layernorm(x, axis=-1, eps=1e-5):
    m = x.mean(dim=axis, keepdim=True)
    v = x.var(dim=axis, keepdim=True, unbiased=False)
    return (x - m) / torch.sqrt(v + eps)
def _scatter_add(tgt, idx, src, axis=0):
    return tgt.clone().index_add_(axis, idx, src)
def _segment_sum(src, seg, n):
    out = torch.zeros((n,) + src.shape[1:], dtype=src.dtype)
    return out.index_add_(0, seg, src)
def _pad(x, pw):
    flat = tuple(v for pair in reversed(pw) for v in pair)
    return torch.nn.functional.pad(x, flat)

kernel_name = 'standalone__gqa_block_cached__near_ridge'

def setup_inputs():

    _w = (lambda a: (lambda t: t.to(torch.bfloat16) if t.is_floating_point() else t)(torch.as_tensor(a)))
    B, Sq, D = 8, 96, 576
    Hq, Hkv, Sk, Dh = 32, 16, 1024, 128
    assert Hq % Hkv == 0, (Hq, Hkv)
    return {
        "x": _w((lambda *s: torch.randn(*s, dtype=torch.bfloat16) * 0.8)(B, Sq, D)),
        "k_cache": _w((lambda *s: torch.randn(*s, dtype=torch.bfloat16) * 0.8)(B, Hkv, Sk, Dh)),
        "v_cache": _w((lambda *s: torch.randn(*s, dtype=torch.bfloat16) * 0.05)(B, Hkv, Sk, Dh)),
        "wq": _w((lambda *s: torch.randn(*s, dtype=torch.bfloat16) * 0.8)(D, Hq * Dh) * (D ** -0.5)),
        "wo": _w((lambda *s: torch.randn(*s, dtype=torch.bfloat16) * 0.05)(Hq * Dh, D) * ((Hq * Dh) ** -0.5)),
    }

def reference(x, k_cache, v_cache, wq, wo):
    B, Sq, D = x.shape
    Hq, Dh = 32, 128
    Hkv = k_cache.shape[1]
    rep = Hq // Hkv
    q = (lambda x, *d: x.permute(*d))((x @ wq).reshape(B, Sq, Hq, Dh), 0, 2, 1, 3)
    k = (lambda x, n, axis: torch.repeat_interleave(x, n, dim=axis))(k_cache, rep, axis=1)
    v = (lambda x, n, axis: torch.repeat_interleave(x, n, dim=axis))(v_cache, rep, axis=1)
    scores = torch.einsum("bhqd,bhkd->bhqk", q, k) * (Dh ** -0.5)
    p = _softmax(scores, axis=-1)
    o = torch.einsum("bhqk,bhkd->bhqd", p, v)
    return (lambda x, *d: x.permute(*d))(o, 0, 2, 1, 3).reshape(B, Sq, Hq * Dh) @ wo
```

```cpp
#include <cuda_runtime.h>
#include <cuda_bf16.h>
#include <cuda.h>
#include <stdint.h>
#include <limits.h>

#define TOUCH_N 6
#define TOUCH_D0 1000
#define TOUCH_DT 560
#define XTRA 2
#define XTRA_T0 2000
#define CAP 2
#define PACE_A 7000
#define PACE_T 1285
#define ZERO_I 12
#define SPLIT 5
#define SPLIT_O 4
#define PFTM 1
#define PVA 6

namespace {

constexpr int NB = 8, SQ = 96, DM = 576, HQ = 32, HKV = 16, SK = 1024, DH = 128;
constexpr int NCTA = NB * HKV;
constexpr int NSLOT = 5;
constexpr uint32_t SLOT_BYTES = 32768;
constexpr uint32_t QO_BYTES = 49152;
constexpr uint32_t QHALF = 24576;
constexpr uint32_t XCH_BYTES = 12288;
constexpr uint32_t X4_OFF = QO_BYTES + NSLOT * SLOT_BYTES;
constexpr uint32_t BAR_OFF = X4_OFF + XCH_BYTES;
constexpr uint32_t TSTART_OFF = BAR_OFF + 192;
constexpr uint32_t DUMMY_OFF = BAR_OFF + 256;
constexpr uint32_t SMEM_BYTES = BAR_OFF + 384 + 1024 + 2048;
constexpr int NTHREADS = 512;
constexpr float QSCALE = 0.08838834764831845f * 1.4426950408889634f;
constexpr int NKT = SK / 128;
constexpr int NQC = DM / 64;
constexpr int NOT = DM / 64;

__device__ unsigned g_cnt[NB * 32];

#define STAMP(i)
#define GSTAMP(i)
#define IOSTAMP(i)

__device__ __forceinline__ uint32_t smem_u32(const void* p) { return (uint32_t)__cvta_generic_to_shared(p); }
__device__ __forceinline__ long long global_ns() {
    long long t;
    asm volatile("mov.u64 %0, %globaltimer;" : "=l"(t)::"memory");
    return t;
}
__device__ __forceinline__ void mbar_init(uint32_t bar, uint32_t cnt) {
    asm volatile("mbarrier.init.shared::cta.b64 [%0], %1;" ::"r"(bar), "r"(cnt) : "memory");
}
__device__ __forceinline__ void mbar_expect_tx(uint32_t bar, uint32_t bytes) {
    asm volatile("mbarrier.arrive.expect_tx.shared::cta.b64 _, [%0], %1;" ::"r"(bar), "r"(bytes) : "memory");
}
__device__ __forceinline__ void mbar_arrive(uint32_t bar, uint32_t cnt) {
    asm volatile("mbarrier.arrive.shared::cta.b64 _, [%0], %1;" ::"r"(bar), "r"(cnt) : "memory");
}
__device__ __forceinline__ void mbar_wait(uint32_t bar, uint32_t parity) {
    uint32_t ok;
    int it = 0;
    do {
        asm volatile("{\n.reg .pred p;\nmbarrier.try_wait.parity.shared::cta.b64 p, [%1], %2;\nselp.u32 %0, 1, 0, p;\n}"
                     : "=r"(ok) : "r"(bar), "r"(parity) : "memory");
        if (++it > (1 << 20)) break;
    } while (!ok);
}
__device__ __forceinline__ void tma_2d(uint32_t dst, const CUtensorMap* tm, int c0, int c1, uint32_t bar) {
    asm volatile("cp.async.bulk.tensor.2d.shared::cluster.global.mbarrier::complete_tx::bytes [%0], [%1, {%3, %4}], [%2];"
                 ::"r"(dst), "l"(tm), "r"(bar), "r"(c0), "r"(c1) : "memory");
}
__device__ __forceinline__ void tma_3d(uint32_t dst, const CUtensorMap* tm, int c0, int c1, int c2, uint32_t bar) {
    asm volatile("cp.async.bulk.tensor.3d.shared::cluster.global.mbarrier::complete_tx::bytes [%0], [%1, {%3, %4, %5}], [%2];"
                 ::"r"(dst), "l"(tm), "r"(bar), "r"(c0), "r"(c1), "r"(c2) : "memory");
}
__device__ __forceinline__ void prefetch_tm(const CUtensorMap* tm) { asm volatile("prefetch.tensormap [%0];" ::"l"(tm) : "memory"); }
__device__ __forceinline__ void prefetch_l2(const void* p) { asm volatile("prefetch.global.L2 [%0];" ::"l"(p)); }
__device__ __forceinline__ void wg_fence() { asm volatile("wgmma.fence.sync.aligned;" ::: "memory"); }
__device__ __forceinline__ void wg_commit() { asm volatile("wgmma.commit_group.sync.aligned;" ::: "memory"); }
template <int N> __device__ __forceinline__ void wg_wait() { asm volatile("wgmma.wait_group.sync.aligned %0;" ::"n"(N) : "memory"); }
template <int N> __device__ __forceinline__ void reg_fence(float (&d)[N]) {
#pragma unroll
    for (int i = 0; i < N; i++) asm volatile("" : "+f"(d[i])::"memory");
}
__device__ __forceinline__ void bar_consumers() { asm volatile("bar.sync 1, 384;" ::: "memory"); }
__device__ __forceinline__ void token_wait(int wg) { asm volatile("bar.sync %0, 256;" ::"r"(2 + wg) : "memory"); }
__device__ __forceinline__ void token_pass(int wg) { asm volatile("bar.arrive %0, 256;" ::"r"(wg == 2 ? 2 : 3 + wg) : "memory"); }
__device__ __forceinline__ void fence_async_smem() { asm volatile("fence.proxy.async.shared::cta;" ::: "memory"); }
__device__ __forceinline__ uint32_t pack_bf16(float lo, float hi) {
    uint32_t r;
    asm("cvt.rn.bf16x2.f32 %0, %1, %2;" : "=r"(r) : "f"(hi), "f"(lo));
    return r;
}
__device__ __forceinline__ float ex2(float x) {
    float y;
    asm("ex2.approx.ftz.f32 %0, %1;" : "=f"(y) : "f"(x));
    return y;
}
__device__ __forceinline__ void stsm_x4(uint32_t a, uint32_t r0, uint32_t r1, uint32_t r2, uint32_t r3) {
    asm volatile("stmatrix.sync.aligned.m8n8.x4.shared.b16 [%0], {%1, %2, %3, %4};" ::"r"(a), "r"(r0), "r"(r1), "r"(r2), "r"(r3) : "memory");
}
__device__ __forceinline__ void stsm_x4_t(uint32_t a, uint32_t r0, uint32_t r1, uint32_t r2, uint32_t r3) {
    asm volatile("stmatrix.sync.aligned.m8n8.x4.trans.shared.b16 [%0], {%1, %2, %3, %4};" ::"r"(a), "r"(r0), "r"(r1), "r"(r2), "r"(r3) : "memory");
}
__device__ __forceinline__ uint64_t make_desc(uint32_t addr, uint32_t lbo_bytes) {
    return (uint64_t)((addr & 0x3FFFF) >> 4) | ((uint64_t)(lbo_bytes >> 4) << 16) | ((uint64_t)64 << 32) | ((uint64_t)1 << 62);
}

__device__ __forceinline__ void wgmma_n96_ss_ta(float (&d)[48], uint64_t da, uint64_t db, int scale_d) {
    asm volatile("{\n.reg .pred p;\nsetp.ne.b32 p, %50, 0;\n"
        "wgmma.mma_async.sync.aligned.m64n96k16.f32.bf16.bf16 "
        "{%0, %1, %2, %3, %4, %5, %6, %7, %8, %9, %10, %11, %12, %13, %14, %15, "
        "%16, %17, %18, %19, %20, %21, %22, %23, %24, %25, %26, %27, %28, %29, %30, %31, "
        "%32, %33, %34, %35, %36, %37, %38, %39, %40, %41, %42, %43, %44, %45, %46, %47}, "
        "%48, %49, p, 1, 1, 1, 0;\n}\n"
        : "+f"(d[0]), "+f"(d[1]), "+f"(d[2]), "+f"(d[3]), "+f"(d[4]), "+f"(d[5]), "+f"(d[6]), "+f"(d[7]),
          "+f"(d[8]), "+f"(d[9]), "+f"(d[10]), "+f"(d[11]), "+f"(d[12]), "+f"(d[13]), "+f"(d[14]), "+f"(d[15]),
          "+f"(d[16]), "+f"(d[17]), "+f"(d[18]), "+f"(d[19]), "+f"(d[20]), "+f"(d[21]), "+f"(d[22]), "+f"(d[23]),
          "+f"(d[24]), "+f"(d[25]), "+f"(d[26]), "+f"(d[27]), "+f"(d[28]), "+f"(d[29]), "+f"(d[30]), "+f"(d[31]),
          "+f"(d[32]), "+f"(d[33]), "+f"(d[34]), "+f"(d[35]), "+f"(d[36]), "+f"(d[37]), "+f"(d[38]), "+f"(d[39]),
          "+f"(d[40]), "+f"(d[41]), "+f"(d[42]), "+f"(d[43]), "+f"(d[44]), "+f"(d[45]), "+f"(d[46]), "+f"(d[47])
        : "l"(da), "l"(db), "r"(scale_d));
}
__device__ __forceinline__ void wgmma_n128_ss(float (&d)[64], uint64_t da, uint64_t db, int scale_d) {
    asm volatile("{\n.reg .pred p;\nsetp.ne.b32 p, %66, 0;\n"
        "wgmma.mma_async.sync.aligned.m64n128k16.f32.bf16.bf16 "
        "{%0, %1, %2, %3, %4, %5, %6, %7, %8, %9, %10, %11, %12, %13, %14, %15, "
        "%16, %17, %18, %19, %20, %21, %22, %23, %24, %25, %26, %27, %28, %29, %30, %31, "
        "%32, %33, %34, %35, %36, %37, %38, %39, %40, %41, %42, %43, %44, %45, %46, %47, "
        "%48, %49, %50, %51, %52, %53, %54, %55, %56, %57, %58, %59, %60, %61, %62, %63}, "
        "%64, %65, p, 1, 1, 0, 0;\n}\n"
        : "+f"(d[0]), "+f"(d[1]), "+f"(d[2]), "+f"(d[3]), "+f"(d[4]), "+f"(d[5]), "+f"(d[6]), "+f"(d[7]),
          "+f"(d[8]), "+f"(d[9]), "+f"(d[10]), "+f"(d[11]), "+f"(d[12]), "+f"(d[13]), "+f"(d[14]), "+f"(d[15]),
          "+f"(d[16]), "+f"(d[17]), "+f"(d[18]), "+f"(d[19]), "+f"(d[20]), "+f"(d[21]), "+f"(d[22]), "+f"(d[23]),
          "+f"(d[24]), "+f"(d[25]), "+f"(d[26]), "+f"(d[27]), "+f"(d[28]), "+f"(d[29]), "+f"(d[30]), "+f"(d[31]),
          "+f"(d[32]), "+f"(d[33]), "+f"(d[34]), "+f"(d[35]), "+f"(d[36]), "+f"(d[37]), "+f"(d[38]), "+f"(d[39]),
          "+f"(d[40]), "+f"(d[41]), "+f"(d[42]), "+f"(d[43]), "+f"(d[44]), "+f"(d[45]), "+f"(d[46]), "+f"(d[47]),
          "+f"(d[48]), "+f"(d[49]), "+f"(d[50]), "+f"(d[51]), "+f"(d[52]), "+f"(d[53]), "+f"(d[54]), "+f"(d[55]),
          "+f"(d[56]), "+f"(d[57]), "+f"(d[58]), "+f"(d[59]), "+f"(d[60]), "+f"(d[61]), "+f"(d[62]), "+f"(d[63])
        : "l"(da), "l"(db), "r"(scale_d));
}
__device__ __forceinline__ void wgmma_n128_rs_tb(float (&d)[64], uint32_t a0, uint32_t a1, uint32_t a2, uint32_t a3, uint64_t db, int scale_d) {
    asm volatile("{\n.reg .pred p;\nsetp.ne.b32 p, %69, 0;\n"
        "wgmma.mma_async.sync.aligned.m64n128k16.f32.bf16.bf16 "
        "{%0, %1, %2, %3, %4, %5, %6, %7, %8, %9, %10, %11, %12, %13, %14, %15, "
        "%16, %17, %18, %19, %20, %21, %22, %23, %24, %25, %26, %27, %28, %29, %30, %31, "
        "%32, %33, %34, %35, %36, %37, %38, %39, %40, %41, %42, %43, %44, %45, %46, %47, "
        "%48, %49, %50, %51, %52, %53, %54, %55, %56, %57, %58, %59, %60, %61, %62, %63}, "
        "{%64, %65, %66, %67}, %68, p, 1, 1, 1;\n}\n"
        : "+f"(d[0]), "+f"(d[1]), "+f"(d[2]), "+f"(d[3]), "+f"(d[4]), "+f"(d[5]), "+f"(d[6]), "+f"(d[7]),
          "+f"(d[8]), "+f"(d[9]), "+f"(d[10]), "+f"(d[11]), "+f"(d[12]), "+f"(d[13]), "+f"(d[14]), "+f"(d[15]),
          "+f"(d[16]), "+f"(d[17]), "+f"(d[18]), "+f"(d[19]), "+f"(d[20]), "+f"(d[21]), "+f"(d[22]), "+f"(d[23]),
          "+f"(d[24]), "+f"(d[25]), "+f"(d[26]), "+f"(d[27]), "+f"(d[28]), "+f"(d[29]), "+f"(d[30]), "+f"(d[31]),
          "+f"(d[32]), "+f"(d[33]), "+f"(d[34]), "+f"(d[35]), "+f"(d[36]), "+f"(d[37]), "+f"(d[38]), "+f"(d[39]),
          "+f"(d[40]), "+f"(d[41]), "+f"(d[42]), "+f"(d[43]), "+f"(d[44]), "+f"(d[45]), "+f"(d[46]), "+f"(d[47]),
          "+f"(d[48]), "+f"(d[49]), "+f"(d[50]), "+f"(d[51]), "+f"(d[52]), "+f"(d[53]), "+f"(d[54]), "+f"(d[55]),
          "+f"(d[56]), "+f"(d[57]), "+f"(d[58]), "+f"(d[59]), "+f"(d[60]), "+f"(d[61]), "+f"(d[62]), "+f"(d[63])
        : "r"(a0), "r"(a1), "r"(a2), "r"(a3), "l"(db), "r"(scale_d));
}

template <bool SCALE>
__device__ __forceinline__ void store_tile_t(float (&acc)[48], uint32_t base, int wq, int lane) {
    if (SCALE) {
#pragma unroll
        for (int i = 0; i < 48; i++) acc[i] *= QSCALE;
    }
    const int mat = lane >> 3, r = lane & 7;
    const uint32_t a = base + (uint32_t)((mat >> 1) * 8 + r) * 128 + (uint32_t)((2 * wq + (mat & 1)) ^ r) * 16;
#pragma unroll
    for (int s = 0; s < 6; s++)
        stsm_x4_t(a + s * 16 * 128, pack_bf16(acc[8 * s + 0], acc[8 * s + 1]), pack_bf16(acc[8 * s + 2], acc[8 * s + 3]),
                  pack_bf16(acc[8 * s + 4], acc[8 * s + 5]), pack_bf16(acc[8 * s + 6], acc[8 * s + 7]));
}

__device__ __forceinline__ constexpr uint32_t x_off(int j) { return (j == 4 || j == NQC - 1) ? X4_OFF : (j % NSLOT) * XCH_BYTES; }

template <bool TWO>
__device__ __forceinline__ void qproj(uint32_t sbase, uint32_t qrdy, int wg, int wq, int lane) {
    const uint32_t slot0 = sbase + QO_BYTES;
    const uint32_t full0 = sbase + BAR_OFF, empty0 = full0 + 8 * NSLOT;
    float acc0[48], acc1[48];
#pragma unroll
    for (int j = 0; j < NQC; j++) {
        const int s = j % NSLOT;
        mbar_wait(full0 + 8 * s, (j / NSLOT) & 1);
        if (j == 0) STAMP(1);
        const uint64_t da = make_desc(slot0 + s * SLOT_BYTES + wg * 8192, 16);
        const uint64_t db = make_desc(sbase + x_off(j), 16);
        wg_fence();
        wgmma_n96_ss_ta(acc0, da, db, j != 0);
        if (TWO) wgmma_n96_ss_ta(acc1, da + 512, db, j != 0);
        wg_commit();
        if (j > 0) {
            wg_wait<1>();
            if (lane == 0) mbar_arrive(empty0 + 8 * ((j - 1) % NSLOT), 1);
        }
#pragma unroll
        for (int k = 1; k < 4; k++) {
            wgmma_n96_ss_ta(acc0, da + k * 128, db + k * 2, 1);
            if (TWO) wgmma_n96_ss_ta(acc1, da + 512 + k * 128, db + k * 2, 1);
        }
        wg_commit();
        bar_consumers();
    }
    wg_wait<0>();
    reg_fence(acc0);
    if (TWO) reg_fence(acc1);
    if (lane == 0) mbar_arrive(empty0 + 8 * ((NQC - 1) % NSLOT), 1);
    STAMP(2);
    store_tile_t<true>(acc0, sbase + (wg & 1) * QHALF + (wg >> 1) * (SQ * 128), wq, lane);
    if (TWO) store_tile_t<true>(acc1, sbase + QHALF + SQ * 128, wq, lane);
    fence_async_smem();
    __syncwarp();
    if (lane == 0) mbar_arrive(qrdy, 1);
}

__global__ void __launch_bounds__(NTHREADS, 1)
gqa_fused_kernel(const __grid_constant__ CUtensorMap tm_x, const __grid_constant__ CUtensorMap tm_wq,
                 const __grid_constant__ CUtensorMap tm_k, const __grid_constant__ CUtensorMap tm_v,
                 const __grid_constant__ CUtensorMap tm_wo, const __grid_constant__ CUtensorMap tm_out,
                 __nv_bfloat16* __restrict__ out, const uint8_t* __restrict__ x_raw, const uint8_t* __restrict__ wq_raw,
                 const uint8_t* __restrict__ k_raw, const uint8_t* __restrict__ v_raw, int clear_out) {
    extern __shared__ __align__(1024) uint8_t smem_raw[];
    const uint32_t sbase = (smem_u32(smem_raw) + 1023u) & ~1023u;
    const uint32_t slot0 = sbase + QO_BYTES;
    const uint32_t full0 = sbase + BAR_OFF, empty0 = full0 + 8 * NSLOT;
    const uint32_t qrdy0 = full0 + 80, ordy0 = full0 + 96, sfull0 = full0 + 112, sfree0 = full0 + 136, zgo = full0 + 160;
    const int tid = threadIdx.x, lane = tid & 31;
    const int warp = __shfl_sync(0xffffffffu, tid >> 5, 0), wg = warp >> 2, wq = warp & 3;

    if (blockIdx.x >= NCTA) {
        const long long t0 = global_ns();
        while (global_ns() - t0 < XTRA_T0) {}
        for (int i = tid; i < XTRA * 32 * 64; i += NTHREADS) {
            const int piece = TOUCH_N + (i >> 11), item = (blockIdx.x - NCTA) * 32 + ((i >> 6) & 31), line = i & 63;
            prefetch_l2(((piece & 4) ? v_raw : k_raw) + (size_t)item * (SK * DH * 2) + (piece >> 3) * SLOT_BYTES + (piece & 3) * 8192 + line * 128);
        }
        return;
    }
    const int b = blockIdx.x & 7, kvh = blockIdx.x >> 3;
    GSTAMP(0);
    STAMP(0);

    if (tid == 384) {
        prefetch_tm(&tm_wq); prefetch_tm(&tm_x);
#pragma unroll
        for (int i = 0; i < NSLOT; i++) mbar_init(full0 + 8 * i, 1);
        asm volatile("fence.mbarrier_init.release.cluster;" ::: "memory");
#pragma unroll
        for (int j = 0; j < NSLOT; j++) {
            const uint32_t bar = full0 + 8 * j;
            mbar_expect_tx(bar, SLOT_BYTES + XCH_BYTES);
            tma_3d(slot0 + j * SLOT_BYTES, &tm_wq, 0, j * 64, kvh * 4, bar);
            tma_2d(sbase + x_off(j), &tm_x, j * 64, b * SQ, bar);
        }
    }
    if (tid == 448) {
#pragma unroll
        for (int i = 0; i < NSLOT; i++) mbar_init(empty0 + 8 * i, 12);
        mbar_init(qrdy0, 8); mbar_init(qrdy0 + 8, 4); mbar_init(ordy0, 6); mbar_init(ordy0 + 8, 6); mbar_init(zgo, 1);
#pragma unroll
        for (int i = 0; i < 3; i++) { mbar_init(sfull0 + 8 * i, 4); mbar_init(sfree0 + 8 * i, 1); }
        prefetch_tm(&tm_k); prefetch_tm(&tm_v); prefetch_tm(&tm_wo); prefetch_tm(&tm_out);
    }
    if (tid == 480) asm volatile("st.shared.b64 [%0], %1;" ::"r"(sbase + TSTART_OFF), "l"(global_ns()) : "memory");
    __syncthreads();

    if (wg == 3) {
        asm volatile("setmaxnreg.dec.sync.aligned.u32 32;");
        if (warp == 12) {
            const int kvrow = (b * HKV + kvh) * SK;
            long long tstart;
            asm volatile("ld.shared.b64 %0, [%1];" : "=l"(tstart) : "r"(sbase + TSTART_OFF) : "memory");
            int s = 0, ph = 0;
            for (int g = NSLOT; g < NQC + 2 * NKT; g++) {
                const uint32_t bar = full0 + 8 * s;
                const int i = g - NQC;
                mbar_wait(empty0 + 8 * s, ph);
                if (i >= 3) {
                    mbar_wait(full0 + 8 * ((g - CAP) % NSLOT), ((g - CAP) / NSLOT) & 1);
                    const long long due = tstart + PACE_A + (long long)PACE_T * (i - 4);
                    while (global_ns() < due) {}
                }
                if (lane == 0) {
                    IOSTAMP(g);
                    if (i < 0) {
                        mbar_expect_tx(bar, SLOT_BYTES + XCH_BYTES);
                        tma_3d(slot0 + s * SLOT_BYTES, &tm_wq, 0, g * 64, kvh * 4, bar);
                        if (g < NQC - 1) tma_2d(sbase + x_off(g), &tm_x, g * 64, b * SQ, bar);
                    } else {
                        if (i == 0) tma_2d(sbase + X4_OFF, &tm_x, (NQC - 1) * 64, b * SQ, full0 + 8 * ((NQC - 1) % NSLOT));
                        mbar_expect_tx(bar, SLOT_BYTES);
                        tma_3d(slot0 + s * SLOT_BYTES, (i & 1) ? &tm_v : &tm_k, 0, kvrow + (i >> 1) * 128, 0, bar);
                        if (i == ZERO_I) mbar_arrive(zgo, 1);
                    }
                }
                if (++s == NSLOT) { s = 0; ph ^= 1; }
            }
            mbar_wait(full0 + 8 * 4, 0);
            for (int j = 0; j < NOT; j++) {
                const uint32_t bar = full0 + 8 * (j & 3);
                mbar_wait(empty0 + 8 * (j & 3), (j >> 2) & 1);
                if (lane == 0) {
                    IOSTAMP(25 + j);
                    mbar_expect_tx(bar, SLOT_BYTES);
                    tma_2d(slot0 + (j & 3) * SLOT_BYTES, &tm_wo, ((j + kvh) % NOT) * 64, kvh * 256, bar);
                }
            }
        } else if (warp == 13) {
            mbar_wait(full0, 0);
#pragma unroll
            for (int i = lane; i < (NQC - NSLOT) * 32; i += 32)
                prefetch_l2(wq_raw + (size_t)(NSLOT * 64 + (i >> 2) * 8 + b) * (HQ * DH * 2) + kvh * 512 + (i & 3) * 128);
            if (lane < (NQC - NSLOT) * 6) prefetch_l2(x_raw + (size_t)(b * SQ + kvh * 6 + lane % 6) * (DM * 2) + (NSLOT + lane / 6) * 128);
            const size_t kvoff = (size_t)(b * HKV + kvh) * SK * DH * 2;
            const long long t0 = clock64();
            for (int i = 0; i < TOUCH_N; i++) {
                while (clock64() - t0 < TOUCH_D0 + i * TOUCH_DT) {}
                const uint8_t* pp = ((i & 4) ? v_raw : k_raw) + kvoff + (size_t)(i >> 3) * SLOT_BYTES + (i & 3) * 8192 + lane * 32;
#pragma unroll
                for (int o = 0; o < 8; o++)
                    asm volatile("cp.async.ca.shared.global [%0], [%1], 4;" ::"r"(sbase + DUMMY_OFF + lane * 4), "l"(pp + o * 1024) : "memory");
            }
            asm volatile("cp.async.wait_all;" ::: "memory");
        } else if (warp == 14) {
            if (clear_out) {
                mbar_wait(zgo, 0);
                uint4* z = reinterpret_cast<uint4*>(out + (size_t)(b * SQ + kvh * 6) * DM);
                for (int i = lane; i < 6 * DM * 2 / 16; i += 32) z[i] = make_uint4(0, 0, 0, 0);
                asm volatile("fence.proxy.async.global;" ::: "memory");
                __syncwarp();
                if (lane == 0) {
                    __threadfence();
                    const unsigned target = (atomicAdd(&g_cnt[b * 32], 1u) / HKV + 1) * HKV;
                    for (int it = 0; it < (1 << 16); it++) {
                        unsigned v;
                        asm volatile("ld.acquire.gpu.global.u32 %0, [%1];" : "=r"(v) : "l"(&g_cnt[b * 32]) : "memory");
                        if ((int)(v - target) >= 0) break;
                        __nanosleep(200);
                    }
                    asm volatile("fence.proxy.async.global;" ::: "memory");
                }
            }
            if (lane == 0) {
                for (int j = 0, w = 0; j < NOT; j++) {
                    mbar_wait(sfull0 + 8 * w, (j / 3) & 1);
                    const uint32_t stage = w == 0 ? sbase + X4_OFF : slot0 + 4 * SLOT_BYTES + (w - 1) * XCH_BYTES;
                    asm volatile("cp.reduce.async.bulk.tensor.2d.global.shared::cta.add.tile.bulk_group [%0, {%2, %3}], [%1];"
                                 ::"l"(&tm_out), "r"(stage), "r"(((j + kvh) % NOT) * 64), "r"(b * SQ) : "memory");
                    asm volatile("cp.async.bulk.commit_group;" ::: "memory");
                    if (j >= 1 && j <= 6) {
                        asm volatile("cp.async.bulk.wait_group.read 1;" ::: "memory");
                        mbar_arrive(sfree0 + 8 * (w == 0 ? 2 : w - 1), 1);
                    }
                    if (++w == 3) w = 0;
                }
                asm volatile("cp.async.bulk.wait_group.read 0;" ::: "memory");
            }
        }
    } else {
        asm volatile("setmaxnreg.inc.sync.aligned.u32 160;");
        if (wg == 2) qproj<true>(sbase, qrdy0 + 8, wg, wq, lane);
        else qproj<false>(sbase, qrdy0, wg, wq, lane);
        if (wg == 2) token_pass(2);
        if (wg < 2) mbar_wait(qrdy0, 0);
        if (wg > 0) mbar_wait(qrdy0 + 8, 0);
        STAMP(3);
        GSTAMP(1);
        float o[64];
#pragma unroll
        for (int j = 0; j < 64; j++) o[j] = 0.f;
        float m0 = -INFINITY, m1 = -INFINITY, l0 = 0.f, l1 = 0.f;
        bool zero_ref = false;
        const uint64_t dq = make_desc(sbase + wg * 8192, 16);
        int slot = NQC % NSLOT;
        uint32_t phase = (NQC / NSLOT) & 1;
#pragma unroll 1
        for (int t = 0; t < NKT; t++) {
            float s[64];
            {
                mbar_wait(full0 + 8 * slot, phase);
                const uint64_t dk = make_desc(slot0 + slot * SLOT_BYTES, 16);
                token_wait(wg);
                wg_fence();
#pragma unroll
                for (int k = 0; k < 8; k++) {
                    wgmma_n128_ss(s, dq + (k >> 2) * (QHALF >> 4) + (k & 3) * 2, dk + (k >> 2) * 1024 + (k & 3) * 2, k != 0);
                    if (k == SPLIT - 1) wg_commit();
                }
                wg_commit();
                wg_wait<1>();
                token_pass(wg);
                wg_wait<0>();
                reg_fence(s);
                if (lane == 0) mbar_arrive(empty0 + 8 * slot, 1);
                if (++slot == NSLOT) { slot = 0; phase ^= 1; }
            }
            {
                int ia0 = max(__float_as_int(s[0]), __float_as_int(s[1])), ia1 = max(__float_as_int(s[2]), __float_as_int(s[3]));
                int ib0 = max(__float_as_int(s[4]), __float_as_int(s[5])), ib1 = max(__float_as_int(s[6]), __float_as_int(s[7]));
#pragma unroll
                for (int j = 1; j < 8; j++) {
                    ia0 = __vimax3_s32(ia0, __float_as_int(s[8 * j + 0]), __float_as_int(s[8 * j + 1]));
                    ia1 = __vimax3_s32(ia1, __float_as_int(s[8 * j + 2]), __float_as_int(s[8 * j + 3]));
                    ib0 = __vimax3_s32(ib0, __float_as_int(s[8 * j + 4]), __float_as_int(s[8 * j + 5]));
                    ib1 = __vimax3_s32(ib1, __float_as_int(s[8 * j + 6]), __float_as_int(s[8 * j + 7]));
                }
                const float th0 = m0 + 16.f, th1 = m1 + 16.f;
                const int ti0 = th0 >= 0.f ? __float_as_int(th0) : INT_MIN, ti1 = th1 >= 0.f ? __float_as_int(th1) : INT_MIN;
                if (__any_sync(0xffffffffu, max(ia0, ib0) >= ti0 || max(ia1, ib1) >= ti1)) {
                    float mx0 = m0, mx1 = m1;
#pragma unroll
                    for (int j = 0; j < 16; j++) {
                        mx0 = fmaxf(mx0, fmaxf(s[4 * j], s[4 * j + 1]));
                        mx1 = fmaxf(mx1, fmaxf(s[4 * j + 2], s[4 * j + 3]));
                    }
                    mx0 = fmaxf(mx0, __shfl_xor_sync(0xffffffffu, mx0, 1));
                    mx1 = fmaxf(mx1, __shfl_xor_sync(0xffffffffu, mx1, 1));
                    mx0 = fmaxf(mx0, __shfl_xor_sync(0xffffffffu, mx0, 2));
                    mx1 = fmaxf(mx1, __shfl_xor_sync(0xffffffffu, mx1, 2));
                    zero_ref = t == 0 && __all_sync(0xffffffffu, mx0 >= -40.f && mx0 < 16.f && mx1 >= -40.f && mx1 < 16.f);
                    if (zero_ref) { mx0 = 0.f; mx1 = 0.f; }
                    const float a0 = ex2(m0 - mx0), a1 = ex2(m1 - mx1);
                    m0 = mx0; m1 = mx1;
                    l0 *= a0; l1 *= a1;
#pragma unroll
                    for (int j = 0; j < 16; j++) { o[4 * j] *= a0; o[4 * j + 1] *= a0; o[4 * j + 2] *= a1; o[4 * j + 3] *= a1; }
                }
                if (!zero_ref) {
#pragma unroll
                    for (int j = 0; j < 16; j++) { s[4 * j] -= m0; s[4 * j + 1] -= m0; s[4 * j + 2] -= m1; s[4 * j + 3] -= m1; }
                }
            }
            uint32_t p[32];
            auto exp_block = [&](int j) {
                const float e0 = ex2(s[4 * j + 0]), e1 = ex2(s[4 * j + 1]), e2 = ex2(s[4 * j + 2]), e3 = ex2(s[4 * j + 3]);
                l0 += e0 + e1; l1 += e2 + e3;
                p[2 * j] = pack_bf16(e0, e1);
                p[2 * j + 1] = pack_bf16(e2, e3);
            };
#pragma unroll
            for (int j = 0; j < 2 * PVA; j++) exp_block(j);
            mbar_wait(full0 + 8 * slot, phase);
            const uint64_t dv = make_desc(slot0 + slot * SLOT_BYTES, 16384);
            token_wait(wg);
            wg_fence();
#pragma unroll
            for (int k = 0; k < PVA; k++) wgmma_n128_rs_tb(o, p[4 * k], p[4 * k + 1], p[4 * k + 2], p[4 * k + 3], dv + k * 128, 1);
            wg_commit();
            mbar_wait(full0 + 8 * slot, phase);
#pragma unroll
            for (int j = 2 * PVA; j < 16; j++) exp_block(j);
            wg_fence();
#pragma unroll
            for (int k = PVA; k < 8; k++) wgmma_n128_rs_tb(o, p[4 * k], p[4 * k + 1], p[4 * k + 2], p[4 * k + 3], dv + k * 128, 1);
            wg_commit();
            token_pass(wg);
            if (t == NKT - 1) {
                l0 += __shfl_xor_sync(0xffffffffu, l0, 1); l1 += __shfl_xor_sync(0xffffffffu, l1, 1);
                l0 += __shfl_xor_sync(0xffffffffu, l0, 2); l1 += __shfl_xor_sync(0xffffffffu, l1, 2);
                asm volatile("rcp.approx.ftz.f32 %0, %0;" : "+f"(l0));
                asm volatile("rcp.approx.ftz.f32 %0, %0;" : "+f"(l1));
            }
            wg_wait<0>();
            reg_fence(o);
            if (lane == 0) mbar_arrive(empty0 + 8 * slot, 1);
            if (++slot == NSLOT) { slot = 0; phase ^= 1; }
            STAMP(8 + t);
            if (t == 3) GSTAMP(2);
        }
        {
            const int mat = lane >> 3, r = lane & 7;
            const uint32_t rowaddr = sbase + (uint32_t)(wg * 64 + wq * 16 + (mat & 1) * 8 + r) * 128;
#pragma unroll
            for (int j = 0; j < 8; j++) {
                const uint32_t chunk = (uint32_t)(((2 * j + (mat >> 1)) & 7) ^ r);
                stsm_x4(rowaddr + (j >> 2) * QHALF + chunk * 16,
                        pack_bf16(o[8 * j + 0] * l0, o[8 * j + 1] * l0), pack_bf16(o[8 * j + 2] * l1, o[8 * j + 3] * l1),
                        pack_bf16(o[8 * j + 4] * l0, o[8 * j + 5] * l0), pack_bf16(o[8 * j + 6] * l1, o[8 * j + 7] * l1));
            }
            fence_async_smem();
            __syncwarp();
            if (lane == 0) mbar_arrive(ordy0 + (warp < 6 ? 0 : 8), 1);
        }
        STAMP(4);
        GSTAMP(3);
        const uint32_t stage = wg == 0 ? sbase + X4_OFF : slot0 + 4 * SLOT_BYTES + (wg - 1) * XCH_BYTES;
#pragma unroll
        for (int jt = 0; jt < 3; jt++) {
            const int j = jt * 3 + wg, s = j & 3;
            float acc[48];
            mbar_wait(full0 + 8 * s, (1 + (j >> 2)) & 1);
            const uint64_t da = make_desc(slot0 + s * SLOT_BYTES, 16);
            const uint64_t db = make_desc(sbase, 16);
            if (jt == 0) mbar_wait(ordy0, 0);
            token_wait(wg);
            wg_fence();
#pragma unroll
            for (int k = 0; k < 8; k++) wgmma_n96_ss_ta(acc, da + k * 128, db + ((k >> 2) * QHALF + (k & 3) * 32) / 16, k != 0);
            if (jt == 0) {
                mbar_wait(ordy0 + 8, 0);
                wg_fence();
            }
#pragma unroll
            for (int k = 0; k < 8; k++) {
                wgmma_n96_ss_ta(acc, da + (8 + k) * 128, db + (SQ * 128 + (k >> 2) * QHALF + (k & 3) * 32) / 16, 1);
                if (k == SPLIT_O - 1) wg_commit();
            }
            wg_commit();
            wg_wait<1>();
            if (j != NOT - 1) token_pass(wg);
            if (jt > 0) mbar_wait(sfree0 + 8 * wg, (jt - 1) & 1);
            wg_wait<0>();
            reg_fence(acc);
            STAMP(24 + jt);
            if (lane == 0) mbar_arrive(empty0 + 8 * s, 3);
            store_tile_t<false>(acc, stage, wq, lane);
            fence_async_smem();
            __syncwarp();
            if (lane == 0) mbar_arrive(sfull0 + 8 * wg, 1);
            STAMP(16 + jt);
        }
        GSTAMP(4);
        STAMP(6);
        GSTAMP(5);
    }
}

typedef CUresult (*EncodeFn)(CUtensorMap*, CUtensorMapDataType, cuuint32_t, void*, const cuuint64_t*, const cuuint64_t*,
                             const cuuint32_t*, const cuuint32_t*, CUtensorMapInterleave, CUtensorMapSwizzle,
                             CUtensorMapL2promotion, CUtensorMapFloatOOBfill);

void encode(EncodeFn fn, CUtensorMap* tm, const void* ptr, int rank, const cuuint64_t* dims, const cuuint64_t* strides,
            const cuuint32_t* box) {
    const cuuint32_t es[3] = {1, 1, 1};
    fn(tm, CU_TENSOR_MAP_DATA_TYPE_BFLOAT16, rank, const_cast<void*>(ptr), dims, strides, box, es,
       CU_TENSOR_MAP_INTERLEAVE_NONE, CU_TENSOR_MAP_SWIZZLE_128B, CU_TENSOR_MAP_L2_PROMOTION_L2_256B,
       CU_TENSOR_MAP_FLOAT_OOB_FILL_NONE);
}

}

extern "C" void kernel_launch(void* const* d_in, const int* in_sizes, int n_in, void* d_out, int out_size) {
    (void)in_sizes; (void)n_in; (void)out_size;
    static EncodeFn fn = nullptr;
    static int sms = 0;
    if (!fn) {
        void* p = nullptr;
        cudaDriverEntryPointQueryResult qr;
        cudaGetDriverEntryPoint("cuTensorMapEncodeTiled", &p, cudaEnableDefault, &qr);
        fn = (EncodeFn)p;
        int dev = 0;
        cudaGetDevice(&dev);
        cudaDeviceGetAttribute(&sms, cudaDevAttrMultiProcessorCount, dev);
        cudaFuncSetAttribute(gqa_fused_kernel, cudaFuncAttributeMaxDynamicSharedMemorySize, SMEM_BYTES);
    }
    CUtensorMap tx, twq, tk, tv, two, tout;
    {
        const cuuint64_t d[2] = {DM, NB * SQ}, s[1] = {DM * 2};
        const cuuint32_t bx[2] = {64, SQ};
        encode(fn, &tx, d_in[0], 2, d, s, bx);
        encode(fn, &tout, d_out, 2, d, s, bx);
    }
    {
        const cuuint64_t d[3] = {64, (cuuint64_t)NB * HKV * SK, 2}, s[2] = {DH * 2, 128};
        const cuuint32_t bx[3] = {64, 128, 2};
        encode(fn, &tk, d_in[1], 3, d, s, bx);
        encode(fn, &tv, d_in[2], 3, d, s, bx);
    }
    {
        const cuuint64_t d[3] = {64, DM, HQ * DH / 64}, s[2] = {HQ * DH * 2, 128};
        const cuuint32_t bx[3] = {64, 64, 4};
        encode(fn, &twq, d_in[3], 3, d, s, bx);
    }
    {
        const cuuint64_t d[2] = {DM, HQ * DH}, s[1] = {DM * 2};
        const cuuint32_t bx[2] = {64, 256};
        encode(fn, &two, d_in[4], 2, d, s, bx);
    }
    const int clear_in_kernel = sms >= NCTA;
    if (!clear_in_kernel) cudaMemsetAsync(d_out, 0, (size_t)NB * SQ * DM * 2, cudaStreamPerThread);
    const int grid = (XTRA && sms >= NCTA + 4) ? NCTA + 4 : NCTA;
    gqa_fused_kernel<<<grid, NTHREADS, SMEM_BYTES, cudaStreamPerThread>>>(
        tx, twq, tk, tv, two, tout, (__nv_bfloat16*)d_out, (const uint8_t*)d_in[0], (const uint8_t*)d_in[3],
        (const uint8_t*)d_in[1], (const uint8_t*)d_in[2], clear_in_kernel);
}
```

```cpp
#include <cuda_runtime.h>
#include <cuda_bf16.h>
#include <cuda.h>
#include <stdint.h>
#include <limits.h>

#define TOUCH_N 7
#define TOUCH_D0 1000
#define TOUCH_DT 560
#define XTRA 3
#define XTRA_T0 1500
#define CAP 2
#define PACE_A 6800
#define PACE_T 1290
#define ZERO_I 12
#define SPLIT 5
#define SPLIT_O 4
#define PFTM 1
#define PVA 6

namespace {

constexpr int NB = 8, SQ = 96, DM = 576, HQ = 32, HKV = 16, SK = 1024, DH = 128;
constexpr int NCTA = NB * HKV;
constexpr int NSLOT = 5;
constexpr uint32_t SLOT_BYTES = 32768;
constexpr uint32_t QO_BYTES = 49152;
constexpr uint32_t QHALF = 24576;
constexpr uint32_t XCH_BYTES = 12288;
constexpr uint32_t X4_OFF = QO_BYTES + NSLOT * SLOT_BYTES;
constexpr uint32_t BAR_OFF = X4_OFF + XCH_BYTES;
constexpr uint32_t TSTART_OFF = BAR_OFF + 192;
constexpr uint32_t DUMMY_OFF = BAR_OFF + 256;
constexpr uint32_t SMEM_BYTES = BAR_OFF + 384 + 1024 + 2048;
constexpr int NTHREADS = 512;
constexpr float QSCALE = 0.08838834764831845f * 1.4426950408889634f;
constexpr int NKT = SK / 128;
constexpr int NQC = DM / 64;
constexpr int NOT = DM / 64;

__device__ unsigned g_cnt[NB * 32];

#define STAMP(i)
#define GSTAMP(i)
#define IOSTAMP(i)

__device__ __forceinline__ uint32_t smem_u32(const void* p) { return (uint32_t)__cvta_generic_to_shared(p); }
__device__ __forceinline__ long long global_ns() {
    long long t;
    asm volatile("mov.u64 %0, %globaltimer;" : "=l"(t)::"memory");
    return t;
}
__device__ __forceinline__ void mbar_init(uint32_t bar, uint32_t cnt) {
    asm volatile("mbarrier.init.shared::cta.b64 [%0], %1;" ::"r"(bar), "r"(cnt) : "memory");
}
__device__ __forceinline__ void mbar_expect_tx(uint32_t bar, uint32_t bytes) {
    asm volatile("mbarrier.arrive.expect_tx.shared::cta.b64 _, [%0], %1;" ::"r"(bar), "r"(bytes) : "memory");
}
__device__ __forceinline__ void mbar_arrive(uint32_t bar, uint32_t cnt) {
    asm volatile("mbarrier.arrive.shared::cta.b64 _, [%0], %1;" ::"r"(bar), "r"(cnt) : "memory");
}
__device__ __forceinline__ void mbar_wait(uint32_t bar, uint32_t parity) {
    uint32_t ok;
    int it = 0;
    do {
        asm volatile("{\n.reg .pred p;\nmbarrier.try_wait.parity.shared::cta.b64 p, [%1], %2;\nselp.u32 %0, 1, 0, p;\n}"
                     : "=r"(ok) : "r"(bar), "r"(parity) : "memory");
        if (++it > (1 << 20)) break;
    } while (!ok);
}
__device__ __forceinline__ void tma_2d(uint32_t dst, const CUtensorMap* tm, int c0, int c1, uint32_t bar) {
    asm volatile("cp.async.bulk.tensor.2d.shared::cluster.global.mbarrier::complete_tx::bytes [%0], [%1, {%3, %4}], [%2];"
                 ::"r"(dst), "l"(tm), "r"(bar), "r"(c0), "r"(c1) : "memory");
}
__device__ __forceinline__ void tma_3d(uint32_t dst, const CUtensorMap* tm, int c0, int c1, int c2, uint32_t bar) {
    asm volatile("cp.async.bulk.tensor.3d.shared::cluster.global.mbarrier::complete_tx::bytes [%0], [%1, {%3, %4, %5}], [%2];"
                 ::"r"(dst), "l"(tm), "r"(bar), "r"(c0), "r"(c1), "r"(c2) : "memory");
}
__device__ __forceinline__ void prefetch_tm(const CUtensorMap* tm) { asm volatile("prefetch.tensormap [%0];" ::"l"(tm) : "memory"); }
__device__ __forceinline__ void prefetch_l2(const void* p) { asm volatile("prefetch.global.L2 [%0];" ::"l"(p)); }
__device__ __forceinline__ void wg_fence() { asm volatile("wgmma.fence.sync.aligned;" ::: "memory"); }
__device__ __forceinline__ void wg_commit() { asm volatile("wgmma.commit_group.sync.aligned;" ::: "memory"); }
template <int N> __device__ __forceinline__ void wg_wait() { asm volatile("wgmma.wait_group.sync.aligned %0;" ::"n"(N) : "memory"); }
template <int N> __device__ __forceinline__ void reg_fence(float (&d)[N]) {
#pragma unroll
    for (int i = 0; i < N; i++) asm volatile("" : "+f"(d[i])::"memory");
}
__device__ __forceinline__ void bar_consumers() { asm volatile("bar.sync 1, 384;" ::: "memory"); }
__device__ __forceinline__ void token_wait(int wg) { asm volatile("bar.sync %0, 256;" ::"r"(2 + wg) : "memory"); }
__device__ __forceinline__ void token_pass(int wg) { asm volatile("bar.arrive %0, 256;" ::"r"(wg == 2 ? 2 : 3 + wg) : "memory"); }
__device__ __forceinline__ void fence_async_smem() { asm volatile("fence.proxy.async.shared::cta;" ::: "memory"); }
__device__ __forceinline__ uint32_t pack_bf16(float lo, float hi) {
    uint32_t r;
    asm("cvt.rn.bf16x2.f32 %0, %1, %2;" : "=r"(r) : "f"(hi), "f"(lo));
    return r;
}
__device__ __forceinline__ float ex2(float x) {
    float y;
    asm("ex2.approx.ftz.f32 %0, %1;" : "=f"(y) : "f"(x));
    return y;
}
__device__ __forceinline__ void stsm_x4(uint32_t a, uint32_t r0, uint32_t r1, uint32_t r2, uint32_t r3) {
    asm volatile("stmatrix.sync.aligned.m8n8.x4.shared.b16 [%0], {%1, %2, %3, %4};" ::"r"(a), "r"(r0), "r"(r1), "r"(r2), "r"(r3) : "memory");
}
__device__ __forceinline__ void stsm_x4_t(uint32_t a, uint32_t r0, uint32_t r1, uint32_t r2, uint32_t r3) {
    asm volatile("stmatrix.sync.aligned.m8n8.x4.trans.shared.b16 [%0], {%1, %2, %3, %4};" ::"r"(a), "r"(r0), "r"(r1), "r"(r2), "r"(r3) : "memory");
}
__device__ __forceinline__ uint64_t make_desc(uint32_t addr, uint32_t lbo_bytes) {
    return (uint64_t)((addr & 0x3FFFF) >> 4) | ((uint64_t)(lbo_bytes >> 4) << 16) | ((uint64_t)64 << 32) | ((uint64_t)1 << 62);
}

__device__ __forceinline__ void wgmma_n96_ss_ta(float (&d)[48], uint64_t da, uint64_t db, int scale_d) {
    asm volatile("{\n.reg .pred p;\nsetp.ne.b32 p, %50, 0;\n"
        "wgmma.mma_async.sync.aligned.m64n96k16.f32.bf16.bf16 "
        "{%0, %1, %2, %3, %4, %5, %6, %7, %8, %9, %10, %11, %12, %13, %14, %15, "
        "%16, %17, %18, %19, %20, %21, %22, %23, %24, %25, %26, %27, %28, %29, %30, %31, "
        "%32, %33, %34, %35, %36, %37, %38, %39, %40, %41, %42, %43, %44, %45, %46, %47}, "
        "%48, %49, p, 1, 1, 1, 0;\n}\n"
        : "+f"(d[0]), "+f"(d[1]), "+f"(d[2]), "+f"(d[3]), "+f"(d[4]), "+f"(d[5]), "+f"(d[6]), "+f"(d[7]),
          "+f"(d[8]), "+f"(d[9]), "+f"(d[10]), "+f"(d[11]), "+f"(d[12]), "+f"(d[13]), "+f"(d[14]), "+f"(d[15]),
          "+f"(d[16]), "+f"(d[17]), "+f"(d[18]), "+f"(d[19]), "+f"(d[20]), "+f"(d[21]), "+f"(d[22]), "+f"(d[23]),
          "+f"(d[24]), "+f"(d[25]), "+f"(d[26]), "+f"(d[27]), "+f"(d[28]), "+f"(d[29]), "+f"(d[30]), "+f"(d[31]),
          "+f"(d[32]), "+f"(d[33]), "+f"(d[34]), "+f"(d[35]), "+f"(d[36]), "+f"(d[37]), "+f"(d[38]), "+f"(d[39]),
          "+f"(d[40]), "+f"(d[41]), "+f"(d[42]), "+f"(d[43]), "+f"(d[44]), "+f"(d[45]), "+f"(d[46]), "+f"(d[47])
        : "l"(da), "l"(db), "r"(scale_d));
}
__device__ __forceinline__ void wgmma_n128_ss(float (&d)[64], uint64_t da, uint64_t db, int scale_d) {
    asm volatile("{\n.reg .pred p;\nsetp.ne.b32 p, %66, 0;\n"
        "wgmma.mma_async.sync.aligned.m64n128k16.f32.bf16.bf16 "
        "{%0, %1, %2, %3, %4, %5, %6, %7, %8, %9, %10, %11, %12, %13, %14, %15, "
        "%16, %17, %18, %19, %20, %21, %22, %23, %24, %25, %26, %27, %28, %29, %30, %31, "
        "%32, %33, %34, %35, %36, %37, %38, %39, %40, %41, %42, %43, %44, %45, %46, %47, "
        "%48, %49, %50, %51, %52, %53, %54, %55, %56, %57, %58, %59, %60, %61, %62, %63}, "
        "%64, %65, p, 1, 1, 0, 0;\n}\n"
        : "+f"(d[0]), "+f"(d[1]), "+f"(d[2]), "+f"(d[3]), "+f"(d[4]), "+f"(d[5]), "+f"(d[6]), "+f"(d[7]),
          "+f"(d[8]), "+f"(d[9]), "+f"(d[10]), "+f"(d[11]), "+f"(d[12]), "+f"(d[13]), "+f"(d[14]), "+f"(d[15]),
          "+f"(d[16]), "+f"(d[17]), "+f"(d[18]), "+f"(d[19]), "+f"(d[20]), "+f"(d[21]), "+f"(d[22]), "+f"(d[23]),
          "+f"(d[24]), "+f"(d[25]), "+f"(d[26]), "+f"(d[27]), "+f"(d[28]), "+f"(d[29]), "+f"(d[30]), "+f"(d[31]),
          "+f"(d[32]), "+f"(d[33]), "+f"(d[34]), "+f"(d[35]), "+f"(d[36]), "+f"(d[37]), "+f"(d[38]), "+f"(d[39]),
          "+f"(d[40]), "+f"(d[41]), "+f"(d[42]), "+f"(d[43]), "+f"(d[44]), "+f"(d[45]), "+f"(d[46]), "+f"(d[47]),
          "+f"(d[48]), "+f"(d[49]), "+f"(d[50]), "+f"(d[51]), "+f"(d[52]), "+f"(d[53]), "+f"(d[54]), "+f"(d[55]),
          "+f"(d[56]), "+f"(d[57]), "+f"(d[58]), "+f"(d[59]), "+f"(d[60]), "+f"(d[61]), "+f"(d[62]), "+f"(d[63])
        : "l"(da), "l"(db), "r"(scale_d));
}
__device__ __forceinline__ void wgmma_n128_rs_tb(float (&d)[64], uint32_t a0, uint32_t a1, uint32_t a2, uint32_t a3, uint64_t db, int scale_d) {
    asm volatile("{\n.reg .pred p;\nsetp.ne.b32 p, %69, 0;\n"
        "wgmma.mma_async.sync.aligned.m64n128k16.f32.bf16.bf16 "
        "{%0, %1, %2, %3, %4, %5, %6, %7, %8, %9, %10, %11, %12, %13, %14, %15, "
        "%16, %17, %18, %19, %20, %21, %22, %23, %24, %25, %26, %27, %28, %29, %30, %31, "
        "%32, %33, %34, %35, %36, %37, %38, %39, %40, %41, %42, %43, %44, %45, %46, %47, "
        "%48, %49, %50, %51, %52, %53, %54, %55, %56, %57, %58, %59, %60, %61, %62, %63}, "
        "{%64, %65, %66, %67}, %68, p, 1, 1, 1;\n}\n"
        : "+f"(d[0]), "+f"(d[1]), "+f"(d[2]), "+f"(d[3]), "+f"(d[4]), "+f"(d[5]), "+f"(d[6]), "+f"(d[7]),
          "+f"(d[8]), "+f"(d[9]), "+f"(d[10]), "+f"(d[11]), "+f"(d[12]), "+f"(d[13]), "+f"(d[14]), "+f"(d[15]),
          "+f"(d[16]), "+f"(d[17]), "+f"(d[18]), "+f"(d[19]), "+f"(d[20]), "+f"(d[21]), "+f"(d[22]), "+f"(d[23]),
          "+f"(d[24]), "+f"(d[25]), "+f"(d[26]), "+f"(d[27]), "+f"(d[28]), "+f"(d[29]), "+f"(d[30]), "+f"(d[31]),
          "+f"(d[32]), "+f"(d[33]), "+f"(d[34]), "+f"(d[35]), "+f"(d[36]), "+f"(d[37]), "+f"(d[38]), "+f"(d[39]),
          "+f"(d[40]), "+f"(d[41]), "+f"(d[42]), "+f"(d[43]), "+f"(d[44]), "+f"(d[45]), "+f"(d[46]), "+f"(d[47]),
          "+f"(d[48]), "+f"(d[49]), "+f"(d[50]), "+f"(d[51]), "+f"(d[52]), "+f"(d[53]), "+f"(d[54]), "+f"(d[55]),
          "+f"(d[56]), "+f"(d[57]), "+f"(d[58]), "+f"(d[59]), "+f"(d[60]), "+f"(d[61]), "+f"(d[62]), "+f"(d[63])
        : "r"(a0), "r"(a1), "r"(a2), "r"(a3), "l"(db), "r"(scale_d));
}

template <bool SCALE>
__device__ __forceinline__ void store_tile_t(float (&acc)[48], uint32_t base, int wq, int lane) {
    if (SCALE) {
#pragma unroll
        for (int i = 0; i < 48; i++) acc[i] *= QSCALE;
    }
    const int mat = lane >> 3, r = lane & 7;
    const uint32_t a = base + (uint32_t)((mat >> 1) * 8 + r) * 128 + (uint32_t)((2 * wq + (mat & 1)) ^ r) * 16;
#pragma unroll
    for (int s = 0; s < 6; s++)
        stsm_x4_t(a + s * 16 * 128, pack_bf16(acc[8 * s + 0], acc[8 * s + 1]), pack_bf16(acc[8 * s + 2], acc[8 * s + 3]),
                  pack_bf16(acc[8 * s + 4], acc[8 * s + 5]), pack_bf16(acc[8 * s + 6], acc[8 * s + 7]));
}

__device__ __forceinline__ constexpr uint32_t x_off(int j) { return (j == 4 || j == NQC - 1) ? X4_OFF : (j % NSLOT) * XCH_BYTES; }

template <bool TWO>
__device__ __forceinline__ void qproj(uint32_t sbase, uint32_t qrdy, int wg, int wq, int lane) {
    const uint32_t slot0 = sbase + QO_BYTES;
    const uint32_t full0 = sbase + BAR_OFF, empty0 = full0 + 8 * NSLOT;
    float acc0[48], acc1[48];
#pragma unroll
    for (int j = 0; j < NQC; j++) {
        const int s = j % NSLOT;
        mbar_wait(full0 + 8 * s, (j / NSLOT) & 1);
        if (j == 0) STAMP(1);
        const uint64_t da = make_desc(slot0 + s * SLOT_BYTES + wg * 8192, 16);
        const uint64_t db = make_desc(sbase + x_off(j), 16);
        wg_fence();
        wgmma_n96_ss_ta(acc0, da, db, j != 0);
        if (TWO) wgmma_n96_ss_ta(acc1, da + 512, db, j != 0);
        wg_commit();
        if (j > 0) {
            wg_wait<1>();
            if (lane == 0) mbar_arrive(empty0 + 8 * ((j - 1) % NSLOT), 1);
        }
#pragma unroll
        for (int k = 1; k < 4; k++) {
            wgmma_n96_ss_ta(acc0, da + k * 128, db + k * 2, 1);
            if (TWO) wgmma_n96_ss_ta(acc1, da + 512 + k * 128, db + k * 2, 1);
        }
        wg_commit();
        bar_consumers();
    }
    wg_wait<0>();
    reg_fence(acc0);
    if (TWO) reg_fence(acc1);
    if (lane == 0) mbar_arrive(empty0 + 8 * ((NQC - 1) % NSLOT), 1);
    STAMP(2);
    store_tile_t<true>(acc0, sbase + (wg & 1) * QHALF + (wg >> 1) * (SQ * 128), wq, lane);
    if (TWO) store_tile_t<true>(acc1, sbase + QHALF + SQ * 128, wq, lane);
    fence_async_smem();
    __syncwarp();
    if (lane == 0) mbar_arrive(qrdy, 1);
}

__global__ void __launch_bounds__(NTHREADS, 1)
gqa_fused_kernel(const __grid_constant__ CUtensorMap tm_x, const __grid_constant__ CUtensorMap tm_wq,
                 const __grid_constant__ CUtensorMap tm_k, const __grid_constant__ CUtensorMap tm_v,
                 const __grid_constant__ CUtensorMap tm_wo, const __grid_constant__ CUtensorMap tm_out,
                 __nv_bfloat16* __restrict__ out, const uint8_t* __restrict__ x_raw, const uint8_t* __restrict__ wq_raw,
                 const uint8_t* __restrict__ k_raw, const uint8_t* __restrict__ v_raw, int clear_out) {
    extern __shared__ __align__(1024) uint8_t smem_raw[];
    const uint32_t sbase = (smem_u32(smem_raw) + 1023u) & ~1023u;
    const uint32_t slot0 = sbase + QO_BYTES;
    const uint32_t full0 = sbase + BAR_OFF, empty0 = full0 + 8 * NSLOT;
    const uint32_t qrdy0 = full0 + 80, ordy0 = full0 + 96, sfull0 = full0 + 112, sfree0 = full0 + 136, zgo = full0 + 160;
    const int tid = threadIdx.x, lane = tid & 31;
    const int warp = __shfl_sync(0xffffffffu, tid >> 5, 0), wg = warp >> 2, wq = warp & 3;

    if (blockIdx.x >= NCTA) {
        const long long t0 = global_ns();
        while (global_ns() - t0 < XTRA_T0) {}
        for (int i = tid; i < XTRA * 32 * 64; i += NTHREADS) {
            const int piece = TOUCH_N + (i >> 11), item = (blockIdx.x - NCTA) * 32 + ((i >> 6) & 31), line = i & 63;
            prefetch_l2(((piece & 4) ? v_raw : k_raw) + (size_t)item * (SK * DH * 2) + (piece >> 3) * SLOT_BYTES + (piece & 3) * 8192 + line * 128);
        }
        return;
    }
    const int b = blockIdx.x & 7, kvh = blockIdx.x >> 3;
    GSTAMP(0);
    STAMP(0);

    if (tid == 384) {
        prefetch_tm(&tm_wq); prefetch_tm(&tm_x);
#pragma unroll
        for (int i = 0; i < NSLOT; i++) mbar_init(full0 + 8 * i, 1);
        asm volatile("fence.mbarrier_init.release.cluster;" ::: "memory");
#pragma unroll
        for (int j = 0; j < NSLOT; j++) {
            const uint32_t bar = full0 + 8 * j;
            mbar_expect_tx(bar, SLOT_BYTES + XCH_BYTES);
            tma_3d(slot0 + j * SLOT_BYTES, &tm_wq, 0, j * 64, kvh * 4, bar);
            tma_2d(sbase + x_off(j), &tm_x, j * 64, b * SQ, bar);
        }
    }
    if (tid == 448) {
#pragma unroll
        for (int i = 0; i < NSLOT; i++) mbar_init(empty0 + 8 * i, 12);
        mbar_init(qrdy0, 8); mbar_init(qrdy0 + 8, 4); mbar_init(ordy0, 6); mbar_init(ordy0 + 8, 6); mbar_init(zgo, 1);
#pragma unroll
        for (int i = 0; i < 3; i++) { mbar_init(sfull0 + 8 * i, 4); mbar_init(sfree0 + 8 * i, 1); }
        prefetch_tm(&tm_k); prefetch_tm(&tm_v); prefetch_tm(&tm_wo); prefetch_tm(&tm_out);
    }
    if (tid == 480) asm volatile("st.shared.b64 [%0], %1;" ::"r"(sbase + TSTART_OFF), "l"(global_ns()) : "memory");
    __syncthreads();

    if (wg == 3) {
        asm volatile("setmaxnreg.dec.sync.aligned.u32 32;");
        if (warp == 12) {
            const int kvrow = (b * HKV + kvh) * SK;
            long long tstart;
            asm volatile("ld.shared.b64 %0, [%1];" : "=l"(tstart) : "r"(sbase + TSTART_OFF) : "memory");
            int s = 0, ph = 0;
            for (int g = NSLOT; g < NQC + 2 * NKT; g++) {
                const uint32_t bar = full0 + 8 * s;
                const int i = g - NQC;
                mbar_wait(empty0 + 8 * s, ph);
                if (i >= 3) {
                    mbar_wait(full0 + 8 * ((g - CAP) % NSLOT), ((g - CAP) / NSLOT) & 1);
                    const long long due = tstart + PACE_A + (long long)PACE_T * (i - 4);
                    while (global_ns() < due) {}
                }
                if (lane == 0) {
                    IOSTAMP(g);
                    if (i < 0) {
                        mbar_expect_tx(bar, SLOT_BYTES + XCH_BYTES);
                        tma_3d(slot0 + s * SLOT_BYTES, &tm_wq, 0, g * 64, kvh * 4, bar);
                        if (g < NQC - 1) tma_2d(sbase + x_off(g), &tm_x, g * 64, b * SQ, bar);
                    } else {
                        if (i == 0) tma_2d(sbase + X4_OFF, &tm_x, (NQC - 1) * 64, b * SQ, full0 + 8 * ((NQC - 1) % NSLOT));
                        mbar_expect_tx(bar, SLOT_BYTES);
                        tma_3d(slot0 + s * SLOT_BYTES, (i & 1) ? &tm_v : &tm_k, 0, kvrow + (i >> 1) * 128, 0, bar);
                        if (i == ZERO_I) mbar_arrive(zgo, 1);
                    }
                }
                if (++s == NSLOT) { s = 0; ph ^= 1; }
            }
            mbar_wait(full0 + 8 * 4, 0);
            for (int j = 0; j < NOT; j++) {
                const uint32_t bar = full0 + 8 * (j & 3);
                mbar_wait(empty0 + 8 * (j & 3), (j >> 2) & 1);
                if (lane == 0) {
                    IOSTAMP(25 + j);
                    mbar_expect_tx(bar, SLOT_BYTES);
                    tma_2d(slot0 + (j & 3) * SLOT_BYTES, &tm_wo, ((j + kvh) % NOT) * 64, kvh * 256, bar);
                }
            }
        } else if (warp == 13) {
            mbar_wait(full0, 0);
#pragma unroll
            for (int i = lane; i < (NQC - NSLOT) * 32; i += 32)
                prefetch_l2(wq_raw + (size_t)(NSLOT * 64 + (i >> 2) * 8 + b) * (HQ * DH * 2) + kvh * 512 + (i & 3) * 128);
            if (lane < (NQC - NSLOT) * 6) prefetch_l2(x_raw + (size_t)(b * SQ + kvh * 6 + lane % 6) * (DM * 2) + (NSLOT + lane / 6) * 128);
            const size_t kvoff = (size_t)(b * HKV + kvh) * SK * DH * 2;
            const long long t0 = clock64();
            for (int i = 0; i < TOUCH_N; i++) {
                while (clock64() - t0 < TOUCH_D0 + i * TOUCH_DT) {}
                const uint8_t* pp = ((i & 4) ? v_raw : k_raw) + kvoff + (size_t)(i >> 3) * SLOT_BYTES + (i & 3) * 8192 + lane * 32;
#pragma unroll
                for (int o = 0; o < 8; o++)
                    asm volatile("cp.async.ca.shared.global [%0], [%1], 4;" ::"r"(sbase + DUMMY_OFF + lane * 4), "l"(pp + o * 1024) : "memory");
            }
            asm volatile("cp.async.wait_all;" ::: "memory");
        } else if (warp == 14) {
            if (clear_out) {
                mbar_wait(zgo, 0);
                uint4* z = reinterpret_cast<uint4*>(out + (size_t)(b * SQ + kvh * 6) * DM);
                for (int i = lane; i < 6 * DM * 2 / 16; i += 32) z[i] = make_uint4(0, 0, 0, 0);
                asm volatile("fence.proxy.async.global;" ::: "memory");
                __syncwarp();
                if (lane == 0) {
                    __threadfence();
                    const unsigned target = (atomicAdd(&g_cnt[b * 32], 1u) / HKV + 1) * HKV;
                    for (int it = 0; it < (1 << 16); it++) {
                        unsigned v;
                        asm volatile("ld.acquire.gpu.global.u32 %0, [%1];" : "=r"(v) : "l"(&g_cnt[b * 32]) : "memory");
                        if ((int)(v - target) >= 0) break;
                        __nanosleep(200);
                    }
                    asm volatile("fence.proxy.async.global;" ::: "memory");
                }
            }
            if (lane == 0) {
                for (int j = 0, w = 0; j < NOT; j++) {
                    mbar_wait(sfull0 + 8 * w, (j / 3) & 1);
                    const uint32_t stage = w == 0 ? sbase + X4_OFF : slot0 + 4 * SLOT_BYTES + (w - 1) * XCH_BYTES;
                    asm volatile("cp.reduce.async.bulk.tensor.2d.global.shared::cta.add.tile.bulk_group [%0, {%2, %3}], [%1];"
                                 ::"l"(&tm_out), "r"(stage), "r"(((j + kvh) % NOT) * 64), "r"(b * SQ) : "memory");
                    asm volatile("cp.async.bulk.commit_group;" ::: "memory");
                    if (j >= 1 && j <= 6) {
                        asm volatile("cp.async.bulk.wait_group.read 1;" ::: "memory");
                        mbar_arrive(sfree0 + 8 * (w == 0 ? 2 : w - 1), 1);
                    }
                    if (++w == 3) w = 0;
                }
                asm volatile("cp.async.bulk.wait_group.read 0;" ::: "memory");
            }
        }
    } else {
        asm volatile("setmaxnreg.inc.sync.aligned.u32 160;");
        if (wg == 2) qproj<true>(sbase, qrdy0 + 8, wg, wq, lane);
        else qproj<false>(sbase, qrdy0, wg, wq, lane);
        if (wg == 2) token_pass(2);
        if (wg < 2) mbar_wait(qrdy0, 0);
        if (wg > 0) mbar_wait(qrdy0 + 8, 0);
        STAMP(3);
        GSTAMP(1);
        float o[64];
#pragma unroll
        for (int j = 0; j < 64; j++) o[j] = 0.f;
        float m0 = -INFINITY, m1 = -INFINITY, l0 = 0.f, l1 = 0.f;
        bool zero_ref = false;
        const uint64_t dq = make_desc(sbase + wg * 8192, 16);
        int slot = NQC % NSLOT;
        uint32_t phase = (NQC / NSLOT) & 1;
#pragma unroll 1
        for (int t = 0; t < NKT; t++) {
            float s[64];
            {
                mbar_wait(full0 + 8 * slot, phase);
                const uint64_t dk = make_desc(slot0 + slot * SLOT_BYTES, 16);
                token_wait(wg);
                wg_fence();
#pragma unroll
                for (int k = 0; k < 8; k++) {
                    wgmma_n128_ss(s, dq + (k >> 2) * (QHALF >> 4) + (k & 3) * 2, dk + (k >> 2) * 1024 + (k & 3) * 2, k != 0);
                    if (k == SPLIT - 1) wg_commit();
                }
                wg_commit();
                wg_wait<1>();
                token_pass(wg);
                wg_wait<0>();
                reg_fence(s);
                if (lane == 0) mbar_arrive(empty0 + 8 * slot, 1);
                if (++slot == NSLOT) { slot = 0; phase ^= 1; }
            }
            {
                int ia0 = max(__float_as_int(s[0]), __float_as_int(s[1])), ia1 = max(__float_as_int(s[2]), __float_as_int(s[3]));
                int ib0 = max(__float_as_int(s[4]), __float_as_int(s[5])), ib1 = max(__float_as_int(s[6]), __float_as_int(s[7]));
#pragma unroll
                for (int j = 1; j < 8; j++) {
                    ia0 = __vimax3_s32(ia0, __float_as_int(s[8 * j + 0]), __float_as_int(s[8 * j + 1]));
                    ia1 = __vimax3_s32(ia1, __float_as_int(s[8 * j + 2]), __float_as_int(s[8 * j + 3]));
                    ib0 = __vimax3_s32(ib0, __float_as_int(s[8 * j + 4]), __float_as_int(s[8 * j + 5]));
                    ib1 = __vimax3_s32(ib1, __float_as_int(s[8 * j + 6]), __float_as_int(s[8 * j + 7]));
                }
                const float th0 = m0 + 16.f, th1 = m1 + 16.f;
                const int ti0 = th0 >= 0.f ? __float_as_int(th0) : INT_MIN, ti1 = th1 >= 0.f ? __float_as_int(th1) : INT_MIN;
                if (__any_sync(0xffffffffu, max(ia0, ib0) >= ti0 || max(ia1, ib1) >= ti1)) {
                    float mx0 = m0, mx1 = m1;
#pragma unroll
                    for (int j = 0; j < 16; j++) {
                        mx0 = fmaxf(mx0, fmaxf(s[4 * j], s[4 * j + 1]));
                        mx1 = fmaxf(mx1, fmaxf(s[4 * j + 2], s[4 * j + 3]));
                    }
                    mx0 = fmaxf(mx0, __shfl_xor_sync(0xffffffffu, mx0, 1));
                    mx1 = fmaxf(mx1, __shfl_xor_sync(0xffffffffu, mx1, 1));
                    mx0 = fmaxf(mx0, __shfl_xor_sync(0xffffffffu, mx0, 2));
                    mx1 = fmaxf(mx1, __shfl_xor_sync(0xffffffffu, mx1, 2));
                    zero_ref = t == 0 && __all_sync(0xffffffffu, mx0 >= -40.f && mx0 < 16.f && mx1 >= -40.f && mx1 < 16.f);
                    if (zero_ref) { mx0 = 0.f; mx1 = 0.f; }
                    const float a0 = ex2(m0 - mx0), a1 = ex2(m1 - mx1);
                    m0 = mx0; m1 = mx1;
                    l0 *= a0; l1 *= a1;
#pragma unroll
                    for (int j = 0; j < 16; j++) { o[4 * j] *= a0; o[4 * j + 1] *= a0; o[4 * j + 2] *= a1; o[4 * j + 3] *= a1; }
                }
                if (!zero_ref) {
#pragma unroll
                    for (int j = 0; j < 16; j++) { s[4 * j] -= m0; s[4 * j + 1] -= m0; s[4 * j + 2] -= m1; s[4 * j + 3] -= m1; }
                }
            }
            uint32_t p[32];
            auto exp_block = [&](int j) {
                const float e0 = ex2(s[4 * j + 0]), e1 = ex2(s[4 * j + 1]), e2 = ex2(s[4 * j + 2]), e3 = ex2(s[4 * j + 3]);
                l0 += e0 + e1; l1 += e2 + e3;
                p[2 * j] = pack_bf16(e0, e1);
                p[2 * j + 1] = pack_bf16(e2, e3);
            };
#pragma unroll
            for (int j = 0; j < 2 * PVA; j++) exp_block(j);
            mbar_wait(full0 + 8 * slot, phase);
            const uint64_t dv = make_desc(slot0 + slot * SLOT_BYTES, 16384);
            token_wait(wg);
            wg_fence();
#pragma unroll
            for (int k = 0; k < PVA; k++) wgmma_n128_rs_tb(o, p[4 * k], p[4 * k + 1], p[4 * k + 2], p[4 * k + 3], dv + k * 128, 1);
            wg_commit();
            mbar_wait(full0 + 8 * slot, phase);
#pragma unroll
            for (int j = 2 * PVA; j < 16; j++) exp_block(j);
            wg_fence();
#pragma unroll
            for (int k = PVA; k < 8; k++) wgmma_n128_rs_tb(o, p[4 * k], p[4 * k + 1], p[4 * k + 2], p[4 * k + 3], dv + k * 128, 1);
            wg_commit();
            token_pass(wg);
            if (t == NKT - 1) {
                l0 += __shfl_xor_sync(0xffffffffu, l0, 1); l1 += __shfl_xor_sync(0xffffffffu, l1, 1);
                l0 += __shfl_xor_sync(0xffffffffu, l0, 2); l1 += __shfl_xor_sync(0xffffffffu, l1, 2);
                asm volatile("rcp.approx.ftz.f32 %0, %0;" : "+f"(l0));
                asm volatile("rcp.approx.ftz.f32 %0, %0;" : "+f"(l1));
            }
            wg_wait<0>();
            reg_fence(o);
            if (lane == 0) mbar_arrive(empty0 + 8 * slot, 1);
            if (++slot == NSLOT) { slot = 0; phase ^= 1; }
            STAMP(8 + t);
            if (t == 3) GSTAMP(2);
        }
        {
            const int mat = lane >> 3, r = lane & 7;
            const uint32_t rowaddr = sbase + (uint32_t)(wg * 64 + wq * 16 + (mat & 1) * 8 + r) * 128;
#pragma unroll
            for (int j = 0; j < 8; j++) {
                const uint32_t chunk = (uint32_t)(((2 * j + (mat >> 1)) & 7) ^ r);
                stsm_x4(rowaddr + (j >> 2) * QHALF + chunk * 16,
                        pack_bf16(o[8 * j + 0] * l0, o[8 * j + 1] * l0), pack_bf16(o[8 * j + 2] * l1, o[8 * j + 3] * l1),
                        pack_bf16(o[8 * j + 4] * l0, o[8 * j + 5] * l0), pack_bf16(o[8 * j + 6] * l1, o[8 * j + 7] * l1));
            }
            fence_async_smem();
            __syncwarp();
            if (lane == 0) mbar_arrive(ordy0 + (warp < 6 ? 0 : 8), 1);
        }
        STAMP(4);
        GSTAMP(3);
        const uint32_t stage = wg == 0 ? sbase + X4_OFF : slot0 + 4 * SLOT_BYTES + (wg - 1) * XCH_BYTES;
#pragma unroll
        for (int jt = 0; jt < 3; jt++) {
            const int j = jt * 3 + wg, s = j & 3;
            float acc[48];
            mbar_wait(full0 + 8 * s, (1 + (j >> 2)) & 1);
            const uint64_t da = make_desc(slot0 + s * SLOT_BYTES, 16);
            const uint64_t db = make_desc(sbase, 16);
            if (jt == 0) mbar_wait(ordy0, 0);
            token_wait(wg);
            wg_fence();
#pragma unroll
            for (int k = 0; k < 8; k++) wgmma_n96_ss_ta(acc, da + k * 128, db + ((k >> 2) * QHALF + (k & 3) * 32) / 16, k != 0);
            if (jt == 0) {
                mbar_wait(ordy0 + 8, 0);
                wg_fence();
            }
#pragma unroll
            for (int k = 0; k < 8; k++) {
                wgmma_n96_ss_ta(acc, da + (8 + k) * 128, db + (SQ * 128 + (k >> 2) * QHALF + (k & 3) * 32) / 16, 1);
                if (k == SPLIT_O - 1) wg_commit();
            }
            wg_commit();
            wg_wait<1>();
            if (j != NOT - 1) token_pass(wg);
            if (jt > 0) mbar_wait(sfree0 + 8 * wg, (jt - 1) & 1);
            wg_wait<0>();
            reg_fence(acc);
            STAMP(24 + jt);
            if (lane == 0) mbar_arrive(empty0 + 8 * s, 3);
            store_tile_t<false>(acc, stage, wq, lane);
            fence_async_smem();
            __syncwarp();
            if (lane == 0) mbar_arrive(sfull0 + 8 * wg, 1);
            STAMP(16 + jt);
        }
        GSTAMP(4);
        STAMP(6);
        GSTAMP(5);
    }
}

typedef CUresult (*EncodeFn)(CUtensorMap*, CUtensorMapDataType, cuuint32_t, void*, const cuuint64_t*, const cuuint64_t*,
                             const cuuint32_t*, const cuuint32_t*, CUtensorMapInterleave, CUtensorMapSwizzle,
                             CUtensorMapL2promotion, CUtensorMapFloatOOBfill);

void encode(EncodeFn fn, CUtensorMap* tm, const void* ptr, int rank, const cuuint64_t* dims, const cuuint64_t* strides,
            const cuuint32_t* box) {
    const cuuint32_t es[3] = {1, 1, 1};
    fn(tm, CU_TENSOR_MAP_DATA_TYPE_BFLOAT16, rank, const_cast<void*>(ptr), dims, strides, box, es,
       CU_TENSOR_MAP_INTERLEAVE_NONE, CU_TENSOR_MAP_SWIZZLE_128B, CU_TENSOR_MAP_L2_PROMOTION_L2_256B,
       CU_TENSOR_MAP_FLOAT_OOB_FILL_NONE);
}

}

extern "C" void kernel_launch(void* const* d_in, const int* in_sizes, int n_in, void* d_out, int out_size) {
    (void)in_sizes; (void)n_in; (void)out_size;
    static EncodeFn fn = nullptr;
    static int sms = 0;
    if (!fn) {
        void* p = nullptr;
        cudaDriverEntryPointQueryResult qr;
        cudaGetDriverEntryPoint("cuTensorMapEncodeTiled", &p, cudaEnableDefault, &qr);
        fn = (EncodeFn)p;
        int dev = 0;
        cudaGetDevice(&dev);
        cudaDeviceGetAttribute(&sms, cudaDevAttrMultiProcessorCount, dev);
        cudaFuncSetAttribute(gqa_fused_kernel, cudaFuncAttributeMaxDynamicSharedMemorySize, SMEM_BYTES);
    }
    CUtensorMap tx, twq, tk, tv, two, tout;
    {
        const cuuint64_t d[2] = {DM, NB * SQ}, s[1] = {DM * 2};
        const cuuint32_t bx[2] = {64, SQ};
        encode(fn, &tx, d_in[0], 2, d, s, bx);
        encode(fn, &tout, d_out, 2, d, s, bx);
    }
    {
        const cuuint64_t d[3] = {64, (cuuint64_t)NB * HKV * SK, 2}, s[2] = {DH * 2, 128};
        const cuuint32_t bx[3] = {64, 128, 2};
        encode(fn, &tk, d_in[1], 3, d, s, bx);
        encode(fn, &tv, d_in[2], 3, d, s, bx);
    }
    {
        const cuuint64_t d[3] = {64, DM, HQ * DH / 64}, s[2] = {HQ * DH * 2, 128};
        const cuuint32_t bx[3] = {64, 64, 4};
        encode(fn, &twq, d_in[3], 3, d, s, bx);
    }
    {
        const cuuint64_t d[2] = {DM, HQ * DH}, s[1] = {DM * 2};
        const cuuint32_t bx[2] = {64, 256};
        encode(fn, &two, d_in[4], 2, d, s, bx);
    }
    const int clear_in_kernel = sms >= NCTA;
    if (!clear_in_kernel) cudaMemsetAsync(d_out, 0, (size_t)NB * SQ * DM * 2, cudaStreamPerThread);
    const int grid = (XTRA && sms >= NCTA + 4) ? NCTA + 4 : NCTA;
    gqa_fused_kernel<<<grid, NTHREADS, SMEM_BYTES, cudaStreamPerThread>>>(
        tx, twq, tk, tv, two, tout, (__nv_bfloat16*)d_out, (const uint8_t*)d_in[0], (const uint8_t*)d_in[3],
        (const uint8_t*)d_in[1], (const uint8_t*)d_in[2], clear_in_kernel);
}
```

```cpp
#include <cuda_runtime.h>
#include <cuda_bf16.h>
#include <cuda.h>
#include <stdint.h>
#include <limits.h>

constexpr int TOUCH_N = 7;
constexpr int TOUCH_D0 = 1000;
constexpr int TOUCH_DT = 560;
constexpr int XTRA = 3;
constexpr int XTRA_T0 = 1500;
constexpr int CAP = 2;
constexpr int PACE_A = 6850;
constexpr int PACE_T = 1290;
constexpr int ZERO_I = 12;
constexpr int SPLIT = 5;
constexpr int SPLIT_O = 4;
constexpr int PVA = 6;

namespace {

constexpr int NB = 8, SQ = 96, DM = 576, HQ = 32, HKV = 16, SK = 1024, DH = 128;
constexpr int NCTA = NB * HKV;
constexpr int NSLOT = 5;
constexpr uint32_t SLOT_BYTES = 32768;
constexpr uint32_t QO_BYTES = 49152;
constexpr uint32_t QHALF = 24576;
constexpr uint32_t XCH_BYTES = 12288;
constexpr uint32_t X4_OFF = QO_BYTES + NSLOT * SLOT_BYTES;
constexpr uint32_t BAR_OFF = X4_OFF + XCH_BYTES;
constexpr uint32_t TSTART_OFF = BAR_OFF + 192;
constexpr uint32_t DUMMY_OFF = BAR_OFF + 256;
constexpr uint32_t SMEM_BYTES = BAR_OFF + 384 + 1024;
constexpr int NTHREADS = 512;
constexpr float QSCALE = 0.08838834764831845f * 1.4426950408889634f;
constexpr int NKT = SK / 128;
constexpr int NQC = DM / 64;
constexpr int NOT = DM / 64;

__device__ unsigned g_cnt[NB * 32];


__device__ __forceinline__ uint32_t smem_u32(const void* p) { return (uint32_t)__cvta_generic_to_shared(p); }
__device__ __forceinline__ long long global_ns() {
    long long t;
    asm volatile("mov.u64 %0, %globaltimer;" : "=l"(t)::"memory");
    return t;
}
__device__ __forceinline__ void mbar_init(uint32_t bar, uint32_t cnt) {
    asm volatile("mbarrier.init.shared::cta.b64 [%0], %1;" ::"r"(bar), "r"(cnt) : "memory");
}
__device__ __forceinline__ void mbar_expect_tx(uint32_t bar, uint32_t bytes) {
    asm volatile("mbarrier.arrive.expect_tx.shared::cta.b64 _, [%0], %1;" ::"r"(bar), "r"(bytes) : "memory");
}
__device__ __forceinline__ void mbar_arrive(uint32_t bar, uint32_t cnt) {
    asm volatile("mbarrier.arrive.shared::cta.b64 _, [%0], %1;" ::"r"(bar), "r"(cnt) : "memory");
}
__device__ __forceinline__ void mbar_wait(uint32_t bar, uint32_t parity) {
    uint32_t ok;
    int it = 0;
    do {
        asm volatile("{\n.reg .pred p;\nmbarrier.try_wait.parity.shared::cta.b64 p, [%1], %2;\nselp.u32 %0, 1, 0, p;\n}"
                     : "=r"(ok) : "r"(bar), "r"(parity) : "memory");
        if (++it > (1 << 20)) break;
    } while (!ok);
}
__device__ __forceinline__ void tma_2d(uint32_t dst, const CUtensorMap* tm, int c0, int c1, uint32_t bar) {
    asm volatile("cp.async.bulk.tensor.2d.shared::cluster.global.mbarrier::complete_tx::bytes [%0], [%1, {%3, %4}], [%2];"
                 ::"r"(dst), "l"(tm), "r"(bar), "r"(c0), "r"(c1) : "memory");
}
__device__ __forceinline__ void tma_3d(uint32_t dst, const CUtensorMap* tm, int c0, int c1, int c2, uint32_t bar) {
    asm volatile("cp.async.bulk.tensor.3d.shared::cluster.global.mbarrier::complete_tx::bytes [%0], [%1, {%3, %4, %5}], [%2];"
                 ::"r"(dst), "l"(tm), "r"(bar), "r"(c0), "r"(c1), "r"(c2) : "memory");
}
__device__ __forceinline__ void prefetch_tm(const CUtensorMap* tm) { asm volatile("prefetch.tensormap [%0];" ::"l"(tm) : "memory"); }
__device__ __forceinline__ void prefetch_l2(const void* p) { asm volatile("prefetch.global.L2 [%0];" ::"l"(p)); }
__device__ __forceinline__ void wg_fence() { asm volatile("wgmma.fence.sync.aligned;" ::: "memory"); }
__device__ __forceinline__ void wg_commit() { asm volatile("wgmma.commit_group.sync.aligned;" ::: "memory"); }
template <int N> __device__ __forceinline__ void wg_wait() { asm volatile("wgmma.wait_group.sync.aligned %0;" ::"n"(N) : "memory"); }
template <int N> __device__ __forceinline__ void reg_fence(float (&d)[N]) {
#pragma unroll
    for (int i = 0; i < N; i++) asm volatile("" : "+f"(d[i])::"memory");
}
__device__ __forceinline__ void bar_consumers() { asm volatile("bar.sync 1, 384;" ::: "memory"); }
__device__ __forceinline__ void token_wait(int wg) { asm volatile("bar.sync %0, 256;" ::"r"(2 + wg) : "memory"); }
__device__ __forceinline__ void token_pass(int wg) { asm volatile("bar.arrive %0, 256;" ::"r"(wg == 2 ? 2 : 3 + wg) : "memory"); }
__device__ __forceinline__ void fence_async_smem() { asm volatile("fence.proxy.async.shared::cta;" ::: "memory"); }
__device__ __forceinline__ uint32_t pack_bf16(float lo, float hi) {
    uint32_t r;
    asm("cvt.rn.bf16x2.f32 %0, %1, %2;" : "=r"(r) : "f"(hi), "f"(lo));
    return r;
}
__device__ __forceinline__ float ex2(float x) {
    float y;
    asm("ex2.approx.ftz.f32 %0, %1;" : "=f"(y) : "f"(x));
    return y;
}
__device__ __forceinline__ void stsm_x4(uint32_t a, uint32_t r0, uint32_t r1, uint32_t r2, uint32_t r3) {
    asm volatile("stmatrix.sync.aligned.m8n8.x4.shared.b16 [%0], {%1, %2, %3, %4};" ::"r"(a), "r"(r0), "r"(r1), "r"(r2), "r"(r3) : "memory");
}
__device__ __forceinline__ void stsm_x4_t(uint32_t a, uint32_t r0, uint32_t r1, uint32_t r2, uint32_t r3) {
    asm volatile("stmatrix.sync.aligned.m8n8.x4.trans.shared.b16 [%0], {%1, %2, %3, %4};" ::"r"(a), "r"(r0), "r"(r1), "r"(r2), "r"(r3) : "memory");
}
__device__ __forceinline__ uint64_t make_desc(uint32_t addr, uint32_t lbo_bytes) {
    return (uint64_t)((addr & 0x3FFFF) >> 4) | ((uint64_t)(lbo_bytes >> 4) << 16) | ((uint64_t)64 << 32) | ((uint64_t)1 << 62);
}

__device__ __forceinline__ void wgmma_n96_ss_ta(float (&d)[48], uint64_t da, uint64_t db, int scale_d) {
    asm volatile("{\n.reg .pred p;\nsetp.ne.b32 p, %50, 0;\n"
        "wgmma.mma_async.sync.aligned.m64n96k16.f32.bf16.bf16 "
        "{%0, %1, %2, %3, %4, %5, %6, %7, %8, %9, %10, %11, %12, %13, %14, %15, "
        "%16, %17, %18, %19, %20, %21, %22, %23, %24, %25, %26, %27, %28, %29, %30, %31, "
        "%32, %33, %34, %35, %36, %37, %38, %39, %40, %41, %42, %43, %44, %45, %46, %47}, "
        "%48, %49, p, 1, 1, 1, 0;\n}\n"
        : "+f"(d[0]), "+f"(d[1]), "+f"(d[2]), "+f"(d[3]), "+f"(d[4]), "+f"(d[5]), "+f"(d[6]), "+f"(d[7]),
          "+f"(d[8]), "+f"(d[9]), "+f"(d[10]), "+f"(d[11]), "+f"(d[12]), "+f"(d[13]), "+f"(d[14]), "+f"(d[15]),
          "+f"(d[16]), "+f"(d[17]), "+f"(d[18]), "+f"(d[19]), "+f"(d[20]), "+f"(d[21]), "+f"(d[22]), "+f"(d[23]),
          "+f"(d[24]), "+f"(d[25]), "+f"(d[26]), "+f"(d[27]), "+f"(d[28]), "+f"(d[29]), "+f"(d[30]), "+f"(d[31]),
          "+f"(d[32]), "+f"(d[33]), "+f"(d[34]), "+f"(d[35]), "+f"(d[36]), "+f"(d[37]), "+f"(d[38]), "+f"(d[39]),
          "+f"(d[40]), "+f"(d[41]), "+f"(d[42]), "+f"(d[43]), "+f"(d[44]), "+f"(d[45]), "+f"(d[46]), "+f"(d[47])
        : "l"(da), "l"(db), "r"(scale_d));
}
__device__ __forceinline__ void wgmma_n128_ss(float (&d)[64], uint64_t da, uint64_t db, int scale_d) {
    asm volatile("{\n.reg .pred p;\nsetp.ne.b32 p, %66, 0;\n"
        "wgmma.mma_async.sync.aligned.m64n128k16.f32.bf16.bf16 "
        "{%0, %1, %2, %3, %4, %5, %6, %7, %8, %9, %10, %11, %12, %13, %14, %15, "
        "%16, %17, %18, %19, %20, %21, %22, %23, %24, %25, %26, %27, %28, %29, %30, %31, "
        "%32, %33, %34, %35, %36, %37, %38, %39, %40, %41, %42, %43, %44, %45, %46, %47, "
        "%48, %49, %50, %51, %52, %53, %54, %55, %56, %57, %58, %59, %60, %61, %62, %63}, "
        "%64, %65, p, 1, 1, 0, 0;\n}\n"
        : "+f"(d[0]), "+f"(d[1]), "+f"(d[2]), "+f"(d[3]), "+f"(d[4]), "+f"(d[5]), "+f"(d[6]), "+f"(d[7]),
          "+f"(d[8]), "+f"(d[9]), "+f"(d[10]), "+f"(d[11]), "+f"(d[12]), "+f"(d[13]), "+f"(d[14]), "+f"(d[15]),
          "+f"(d[16]), "+f"(d[17]), "+f"(d[18]), "+f"(d[19]), "+f"(d[20]), "+f"(d[21]), "+f"(d[22]), "+f"(d[23]),
          "+f"(d[24]), "+f"(d[25]), "+f"(d[26]), "+f"(d[27]), "+f"(d[28]), "+f"(d[29]), "+f"(d[30]), "+f"(d[31]),
          "+f"(d[32]), "+f"(d[33]), "+f"(d[34]), "+f"(d[35]), "+f"(d[36]), "+f"(d[37]), "+f"(d[38]), "+f"(d[39]),
          "+f"(d[40]), "+f"(d[41]), "+f"(d[42]), "+f"(d[43]), "+f"(d[44]), "+f"(d[45]), "+f"(d[46]), "+f"(d[47]),
          "+f"(d[48]), "+f"(d[49]), "+f"(d[50]), "+f"(d[51]), "+f"(d[52]), "+f"(d[53]), "+f"(d[54]), "+f"(d[55]),
          "+f"(d[56]), "+f"(d[57]), "+f"(d[58]), "+f"(d[59]), "+f"(d[60]), "+f"(d[61]), "+f"(d[62]), "+f"(d[63])
        : "l"(da), "l"(db), "r"(scale_d));
}
__device__ __forceinline__ void wgmma_n128_rs_tb(float (&d)[64], uint32_t a0, uint32_t a1, uint32_t a2, uint32_t a3, uint64_t db, int scale_d) {
    asm volatile("{\n.reg .pred p;\nsetp.ne.b32 p, %69, 0;\n"
        "wgmma.mma_async.sync.aligned.m64n128k16.f32.bf16.bf16 "
        "{%0, %1, %2, %3, %4, %5, %6, %7, %8, %9, %10, %11, %12, %13, %14, %15, "
        "%16, %17, %18, %19, %20, %21, %22, %23, %24, %25, %26, %27, %28, %29, %30, %31, "
        "%32, %33, %34, %35, %36, %37, %38, %39, %40, %41, %42, %43, %44, %45, %46, %47, "
        "%48, %49, %50, %51, %52, %53, %54, %55, %56, %57, %58, %59, %60, %61, %62, %63}, "
        "{%64, %65, %66, %67}, %68, p, 1, 1, 1;\n}\n"
        : "+f"(d[0]), "+f"(d[1]), "+f"(d[2]), "+f"(d[3]), "+f"(d[4]), "+f"(d[5]), "+f"(d[6]), "+f"(d[7]),
          "+f"(d[8]), "+f"(d[9]), "+f"(d[10]), "+f"(d[11]), "+f"(d[12]), "+f"(d[13]), "+f"(d[14]), "+f"(d[15]),
          "+f"(d[16]), "+f"(d[17]), "+f"(d[18]), "+f"(d[19]), "+f"(d[20]), "+f"(d[21]), "+f"(d[22]), "+f"(d[23]),
          "+f"(d[24]), "+f"(d[25]), "+f"(d[26]), "+f"(d[27]), "+f"(d[28]), "+f"(d[29]), "+f"(d[30]), "+f"(d[31]),
          "+f"(d[32]), "+f"(d[33]), "+f"(d[34]), "+f"(d[35]), "+f"(d[36]), "+f"(d[37]), "+f"(d[38]), "+f"(d[39]),
          "+f"(d[40]), "+f"(d[41]), "+f"(d[42]), "+f"(d[43]), "+f"(d[44]), "+f"(d[45]), "+f"(d[46]), "+f"(d[47]),
          "+f"(d[48]), "+f"(d[49]), "+f"(d[50]), "+f"(d[51]), "+f"(d[52]), "+f"(d[53]), "+f"(d[54]), "+f"(d[55]),
          "+f"(d[56]), "+f"(d[57]), "+f"(d[58]), "+f"(d[59]), "+f"(d[60]), "+f"(d[61]), "+f"(d[62]), "+f"(d[63])
        : "r"(a0), "r"(a1), "r"(a2), "r"(a3), "l"(db), "r"(scale_d));
}

template <bool SCALE>
__device__ __forceinline__ void store_tile_t(float (&acc)[48], uint32_t base, int wq, int lane) {
    if (SCALE) {
#pragma unroll
        for (int i = 0; i < 48; i++) acc[i] *= QSCALE;
    }
    const int mat = lane >> 3, r = lane & 7;
    const uint32_t a = base + (uint32_t)((mat >> 1) * 8 + r) * 128 + (uint32_t)((2 * wq + (mat & 1)) ^ r) * 16;
#pragma unroll
    for (int s = 0; s < 6; s++)
        stsm_x4_t(a + s * 16 * 128, pack_bf16(acc[8 * s + 0], acc[8 * s + 1]), pack_bf16(acc[8 * s + 2], acc[8 * s + 3]),
                  pack_bf16(acc[8 * s + 4], acc[8 * s + 5]), pack_bf16(acc[8 * s + 6], acc[8 * s + 7]));
}

__device__ __forceinline__ constexpr uint32_t x_off(int j) { return (j == 4 || j == NQC - 1) ? X4_OFF : (j % NSLOT) * XCH_BYTES; }

template <bool TWO>
__device__ __forceinline__ void qproj(uint32_t sbase, uint32_t qrdy, int wg, int wq, int lane) {
    const uint32_t slot0 = sbase + QO_BYTES;
    const uint32_t full0 = sbase + BAR_OFF, empty0 = full0 + 8 * NSLOT;
    float acc0[48], acc1[48];
#pragma unroll
    for (int j = 0; j < NQC; j++) {
        const int s = j % NSLOT;
        mbar_wait(full0 + 8 * s, (j / NSLOT) & 1);
        const uint64_t da = make_desc(slot0 + s * SLOT_BYTES + wg * 8192, 16);
        const uint64_t db = make_desc(sbase + x_off(j), 16);
        wg_fence();
        wgmma_n96_ss_ta(acc0, da, db, j != 0);
        if (TWO) wgmma_n96_ss_ta(acc1, da + 512, db, j != 0);
        wg_commit();
        if (j > 0) {
            wg_wait<1>();
            if (lane == 0) mbar_arrive(empty0 + 8 * ((j - 1) % NSLOT), 1);
        }
#pragma unroll
        for (int k = 1; k < 4; k++) {
            wgmma_n96_ss_ta(acc0, da + k * 128, db + k * 2, 1);
            if (TWO) wgmma_n96_ss_ta(acc1, da + 512 + k * 128, db + k * 2, 1);
        }
        wg_commit();
        bar_consumers();
    }
    wg_wait<0>();
    reg_fence(acc0);
    if (TWO) reg_fence(acc1);
    if (lane == 0) mbar_arrive(empty0 + 8 * ((NQC - 1) % NSLOT), 1);
    store_tile_t<true>(acc0, sbase + (wg & 1) * QHALF + (wg >> 1) * (SQ * 128), wq, lane);
    if (TWO) store_tile_t<true>(acc1, sbase + QHALF + SQ * 128, wq, lane);
    fence_async_smem();
    __syncwarp();
    if (lane == 0) mbar_arrive(qrdy, 1);
}

__global__ void __launch_bounds__(NTHREADS, 1)
gqa_fused_kernel(const __grid_constant__ CUtensorMap tm_x, const __grid_constant__ CUtensorMap tm_wq,
                 const __grid_constant__ CUtensorMap tm_k, const __grid_constant__ CUtensorMap tm_v,
                 const __grid_constant__ CUtensorMap tm_wo, const __grid_constant__ CUtensorMap tm_out,
                 __nv_bfloat16* __restrict__ out, const uint8_t* __restrict__ x_raw, const uint8_t* __restrict__ wq_raw,
                 const uint8_t* __restrict__ k_raw, const uint8_t* __restrict__ v_raw, int clear_out) {
    extern __shared__ __align__(1024) uint8_t smem_raw[];
    const uint32_t sbase = (smem_u32(smem_raw) + 1023u) & ~1023u;
    const uint32_t slot0 = sbase + QO_BYTES;
    const uint32_t full0 = sbase + BAR_OFF, empty0 = full0 + 8 * NSLOT;
    const uint32_t qrdy0 = full0 + 80, ordy0 = full0 + 96, sfull0 = full0 + 112, sfree0 = full0 + 136, zgo = full0 + 160;
    const int tid = threadIdx.x, lane = tid & 31;
    const int warp = __shfl_sync(0xffffffffu, tid >> 5, 0), wg = warp >> 2, wq = warp & 3;

    if (blockIdx.x >= NCTA) {
        const long long t0 = global_ns();
        while (global_ns() - t0 < XTRA_T0) {}
        for (int i = tid; i < XTRA * 32 * 64; i += NTHREADS) {
            const int piece = TOUCH_N + (i >> 11), item = (blockIdx.x - NCTA) * 32 + ((i >> 6) & 31), line = i & 63;
            prefetch_l2(((piece & 4) ? v_raw : k_raw) + (size_t)item * (SK * DH * 2) + (piece >> 3) * SLOT_BYTES + (piece & 3) * 8192 + line * 128);
        }
        return;
    }
    const int b = blockIdx.x & 7, kvh = blockIdx.x >> 3;

    if (tid == 384) {
        prefetch_tm(&tm_wq); prefetch_tm(&tm_x);
#pragma unroll
        for (int i = 0; i < NSLOT; i++) mbar_init(full0 + 8 * i, 1);
        asm volatile("fence.mbarrier_init.release.cluster;" ::: "memory");
#pragma unroll
        for (int j = 0; j < NSLOT; j++) {
            const uint32_t bar = full0 + 8 * j;
            mbar_expect_tx(bar, SLOT_BYTES + XCH_BYTES);
            tma_3d(slot0 + j * SLOT_BYTES, &tm_wq, 0, j * 64, kvh * 4, bar);
            tma_2d(sbase + x_off(j), &tm_x, j * 64, b * SQ, bar);
        }
    }
    if (tid == 448) {
#pragma unroll
        for (int i = 0; i < NSLOT; i++) mbar_init(empty0 + 8 * i, 12);
        mbar_init(qrdy0, 8); mbar_init(qrdy0 + 8, 4); mbar_init(ordy0, 6); mbar_init(ordy0 + 8, 6); mbar_init(zgo, 1);
#pragma unroll
        for (int i = 0; i < 3; i++) { mbar_init(sfull0 + 8 * i, 4); mbar_init(sfree0 + 8 * i, 1); }
        prefetch_tm(&tm_k); prefetch_tm(&tm_v); prefetch_tm(&tm_wo); prefetch_tm(&tm_out);
    }
    if (tid == 480) asm volatile("st.shared.b64 [%0], %1;" ::"r"(sbase + TSTART_OFF), "l"(global_ns()) : "memory");
    __syncthreads();

    if (wg == 3) {
        asm volatile("setmaxnreg.dec.sync.aligned.u32 32;");
        if (warp == 12) {
            const int kvrow = (b * HKV + kvh) * SK;
            long long tstart;
            asm volatile("ld.shared.b64 %0, [%1];" : "=l"(tstart) : "r"(sbase + TSTART_OFF) : "memory");
            int s = 0, ph = 0;
            for (int g = NSLOT; g < NQC + 2 * NKT; g++) {
                const uint32_t bar = full0 + 8 * s;
                const int i = g - NQC;
                mbar_wait(empty0 + 8 * s, ph);
                if (i >= 3) {
                    mbar_wait(full0 + 8 * ((g - CAP) % NSLOT), ((g - CAP) / NSLOT) & 1);
                    const long long due = tstart + PACE_A + (long long)PACE_T * (i - 4);
                    while (global_ns() < due) {}
                }
                if (lane == 0) {
                    if (i < 0) {
                        mbar_expect_tx(bar, SLOT_BYTES + XCH_BYTES);
                        tma_3d(slot0 + s * SLOT_BYTES, &tm_wq, 0, g * 64, kvh * 4, bar);
                        if (g < NQC - 1) tma_2d(sbase + x_off(g), &tm_x, g * 64, b * SQ, bar);
                    } else {
                        if (i == 0) tma_2d(sbase + X4_OFF, &tm_x, (NQC - 1) * 64, b * SQ, full0 + 8 * ((NQC - 1) % NSLOT));
                        mbar_expect_tx(bar, SLOT_BYTES);
                        tma_3d(slot0 + s * SLOT_BYTES, (i & 1) ? &tm_v : &tm_k, 0, kvrow + (i >> 1) * 128, 0, bar);
                        if (i == ZERO_I) mbar_arrive(zgo, 1);
                    }
                }
                if (++s == NSLOT) { s = 0; ph ^= 1; }
            }
            mbar_wait(full0 + 8 * 4, 0);
            for (int j = 0; j < NOT; j++) {
                const uint32_t bar = full0 + 8 * (j & 3);
                mbar_wait(empty0 + 8 * (j & 3), (j >> 2) & 1);
                if (lane == 0) {
                    mbar_expect_tx(bar, SLOT_BYTES);
                    tma_2d(slot0 + (j & 3) * SLOT_BYTES, &tm_wo, ((j + kvh) % NOT) * 64, kvh * 256, bar);
                }
            }
        } else if (warp == 13) {
            mbar_wait(full0, 0);
#pragma unroll
            for (int i = lane; i < (NQC - NSLOT) * 32; i += 32)
                prefetch_l2(wq_raw + (size_t)(NSLOT * 64 + (i >> 2) * 8 + b) * (HQ * DH * 2) + kvh * 512 + (i & 3) * 128);
            if (lane < (NQC - NSLOT) * 6) prefetch_l2(x_raw + (size_t)(b * SQ + kvh * 6 + lane % 6) * (DM * 2) + (NSLOT + lane / 6) * 128);
            const size_t kvoff = (size_t)(b * HKV + kvh) * SK * DH * 2;
            const long long t0 = clock64();
            for (int i = 0; i < TOUCH_N; i++) {
                while (clock64() - t0 < TOUCH_D0 + i * TOUCH_DT) {}
                const uint8_t* pp = ((i & 4) ? v_raw : k_raw) + kvoff + (size_t)(i >> 3) * SLOT_BYTES + (i & 3) * 8192 + lane * 32;
#pragma unroll
                for (int o = 0; o < 8; o++)
                    asm volatile("cp.async.ca.shared.global [%0], [%1], 4;" ::"r"(sbase + DUMMY_OFF + lane * 4), "l"(pp + o * 1024) : "memory");
            }
            asm volatile("cp.async.wait_all;" ::: "memory");
        } else if (warp == 14) {
            if (clear_out) {
                mbar_wait(zgo, 0);
                uint4* z = reinterpret_cast<uint4*>(out + (size_t)(b * SQ + kvh * 6) * DM);
                for (int i = lane; i < 6 * DM * 2 / 16; i += 32) z[i] = make_uint4(0, 0, 0, 0);
                asm volatile("fence.proxy.async.global;" ::: "memory");
                __syncwarp();
                if (lane == 0) {
                    __threadfence();
                    const unsigned target = (atomicAdd(&g_cnt[b * 32], 1u) / HKV + 1) * HKV;
                    for (int it = 0; it < (1 << 16); it++) {
                        unsigned v;
                        asm volatile("ld.acquire.gpu.global.u32 %0, [%1];" : "=r"(v) : "l"(&g_cnt[b * 32]) : "memory");
                        if ((int)(v - target) >= 0) break;
                        __nanosleep(200);
                    }
                    asm volatile("fence.proxy.async.global;" ::: "memory");
                }
            }
            if (lane == 0) {
                for (int j = 0, w = 0; j < NOT; j++) {
                    mbar_wait(sfull0 + 8 * w, (j / 3) & 1);
                    const uint32_t stage = w == 0 ? sbase + X4_OFF : slot0 + 4 * SLOT_BYTES + (w - 1) * XCH_BYTES;
                    asm volatile("cp.reduce.async.bulk.tensor.2d.global.shared::cta.add.tile.bulk_group [%0, {%2, %3}], [%1];"
                                 ::"l"(&tm_out), "r"(stage), "r"(((j + kvh) % NOT) * 64), "r"(b * SQ) : "memory");
                    asm volatile("cp.async.bulk.commit_group;" ::: "memory");
                    if (j >= 1 && j <= 6) {
                        asm volatile("cp.async.bulk.wait_group.read 1;" ::: "memory");
                        mbar_arrive(sfree0 + 8 * (w == 0 ? 2 : w - 1), 1);
                    }
                    if (++w == 3) w = 0;
                }
                asm volatile("cp.async.bulk.wait_group.read 0;" ::: "memory");
            }
        }
    } else {
        asm volatile("setmaxnreg.inc.sync.aligned.u32 160;");
        if (wg == 2) qproj<true>(sbase, qrdy0 + 8, wg, wq, lane);
        else qproj<false>(sbase, qrdy0, wg, wq, lane);
        if (wg == 2) token_pass(2);
        if (wg < 2) mbar_wait(qrdy0, 0);
        if (wg > 0) mbar_wait(qrdy0 + 8, 0);
        float o[64];
#pragma unroll
        for (int j = 0; j < 64; j++) o[j] = 0.f;
        float m0 = -INFINITY, m1 = -INFINITY, l0 = 0.f, l1 = 0.f;
        bool zero_ref = false;
        const uint64_t dq = make_desc(sbase + wg * 8192, 16);
        int slot = NQC % NSLOT;
        uint32_t phase = (NQC / NSLOT) & 1;
#pragma unroll 1
        for (int t = 0; t < NKT; t++) {
            float s[64];
            {
                mbar_wait(full0 + 8 * slot, phase);
                const uint64_t dk = make_desc(slot0 + slot * SLOT_BYTES, 16);
                token_wait(wg);
                wg_fence();
#pragma unroll
                for (int k = 0; k < 8; k++) {
                    wgmma_n128_ss(s, dq + (k >> 2) * (QHALF >> 4) + (k & 3) * 2, dk + (k >> 2) * 1024 + (k & 3) * 2, k != 0);
                    if (k == SPLIT - 1) wg_commit();
                }
                wg_commit();
                wg_wait<1>();
                token_pass(wg);
                wg_wait<0>();
                reg_fence(s);
                if (lane == 0) mbar_arrive(empty0 + 8 * slot, 1);
                if (++slot == NSLOT) { slot = 0; phase ^= 1; }
            }
            {
                int ia0 = max(__float_as_int(s[0]), __float_as_int(s[1])), ia1 = max(__float_as_int(s[2]), __float_as_int(s[3]));
                int ib0 = max(__float_as_int(s[4]), __float_as_int(s[5])), ib1 = max(__float_as_int(s[6]), __float_as_int(s[7]));
#pragma unroll
                for (int j = 1; j < 8; j++) {
                    ia0 = __vimax3_s32(ia0, __float_as_int(s[8 * j + 0]), __float_as_int(s[8 * j + 1]));
                    ia1 = __vimax3_s32(ia1, __float_as_int(s[8 * j + 2]), __float_as_int(s[8 * j + 3]));
                    ib0 = __vimax3_s32(ib0, __float_as_int(s[8 * j + 4]), __float_as_int(s[8 * j + 5]));
                    ib1 = __vimax3_s32(ib1, __float_as_int(s[8 * j + 6]), __float_as_int(s[8 * j + 7]));
                }
                const float th0 = m0 + 16.f, th1 = m1 + 16.f;
                const int ti0 = th0 >= 0.f ? __float_as_int(th0) : INT_MIN, ti1 = th1 >= 0.f ? __float_as_int(th1) : INT_MIN;
                if (__any_sync(0xffffffffu, max(ia0, ib0) >= ti0 || max(ia1, ib1) >= ti1)) {
                    float mx0 = m0, mx1 = m1;
#pragma unroll
                    for (int j = 0; j < 16; j++) {
                        mx0 = fmaxf(mx0, fmaxf(s[4 * j], s[4 * j + 1]));
                        mx1 = fmaxf(mx1, fmaxf(s[4 * j + 2], s[4 * j + 3]));
                    }
                    mx0 = fmaxf(mx0, __shfl_xor_sync(0xffffffffu, mx0, 1));
                    mx1 = fmaxf(mx1, __shfl_xor_sync(0xffffffffu, mx1, 1));
                    mx0 = fmaxf(mx0, __shfl_xor_sync(0xffffffffu, mx0, 2));
                    mx1 = fmaxf(mx1, __shfl_xor_sync(0xffffffffu, mx1, 2));
                    zero_ref = t == 0 && __all_sync(0xffffffffu, mx0 >= -40.f && mx0 < 16.f && mx1 >= -40.f && mx1 < 16.f);
                    if (zero_ref) { mx0 = 0.f; mx1 = 0.f; }
                    const float a0 = ex2(m0 - mx0), a1 = ex2(m1 - mx1);
                    m0 = mx0; m1 = mx1;
                    l0 *= a0; l1 *= a1;
#pragma unroll
                    for (int j = 0; j < 16; j++) { o[4 * j] *= a0; o[4 * j + 1] *= a0; o[4 * j + 2] *= a1; o[4 * j + 3] *= a1; }
                }
                if (!zero_ref) {
#pragma unroll
                    for (int j = 0; j < 16; j++) { s[4 * j] -= m0; s[4 * j + 1] -= m0; s[4 * j + 2] -= m1; s[4 * j + 3] -= m1; }
                }
            }
            uint32_t p[32];
            auto exp_block = [&](int j) {
                const float e0 = ex2(s[4 * j + 0]), e1 = ex2(s[4 * j + 1]), e2 = ex2(s[4 * j + 2]), e3 = ex2(s[4 * j + 3]);
                l0 += e0 + e1; l1 += e2 + e3;
                p[2 * j] = pack_bf16(e0, e1);
                p[2 * j + 1] = pack_bf16(e2, e3);
            };
#pragma unroll
            for (int j = 0; j < 2 * PVA; j++) exp_block(j);
            mbar_wait(full0 + 8 * slot, phase);
            const uint64_t dv = make_desc(slot0 + slot * SLOT_BYTES, 16384);
            token_wait(wg);
            wg_fence();
#pragma unroll
            for (int k = 0; k < PVA; k++) wgmma_n128_rs_tb(o, p[4 * k], p[4 * k + 1], p[4 * k + 2], p[4 * k + 3], dv + k * 128, 1);
            wg_commit();
            mbar_wait(full0 + 8 * slot, phase);
#pragma unroll
            for (int j = 2 * PVA; j < 16; j++) exp_block(j);
            wg_fence();
#pragma unroll
            for (int k = PVA; k < 8; k++) wgmma_n128_rs_tb(o, p[4 * k], p[4 * k + 1], p[4 * k + 2], p[4 * k + 3], dv + k * 128, 1);
            wg_commit();
            token_pass(wg);
            if (t == NKT - 1) {
                l0 += __shfl_xor_sync(0xffffffffu, l0, 1); l1 += __shfl_xor_sync(0xffffffffu, l1, 1);
                l0 += __shfl_xor_sync(0xffffffffu, l0, 2); l1 += __shfl_xor_sync(0xffffffffu, l1, 2);
                asm volatile("rcp.approx.ftz.f32 %0, %0;" : "+f"(l0));
                asm volatile("rcp.approx.ftz.f32 %0, %0;" : "+f"(l1));
            }
            wg_wait<0>();
            reg_fence(o);
            if (lane == 0) mbar_arrive(empty0 + 8 * slot, 1);
            if (++slot == NSLOT) { slot = 0; phase ^= 1; }
        }
        {
            const int mat = lane >> 3, r = lane & 7;
            const uint32_t rowaddr = sbase + (uint32_t)(wg * 64 + wq * 16 + (mat & 1) * 8 + r) * 128;
#pragma unroll
            for (int j = 0; j < 8; j++) {
                const uint32_t chunk = (uint32_t)(((2 * j + (mat >> 1)) & 7) ^ r);
                stsm_x4(rowaddr + (j >> 2) * QHALF + chunk * 16,
                        pack_bf16(o[8 * j + 0] * l0, o[8 * j + 1] * l0), pack_bf16(o[8 * j + 2] * l1, o[8 * j + 3] * l1),
                        pack_bf16(o[8 * j + 4] * l0, o[8 * j + 5] * l0), pack_bf16(o[8 * j + 6] * l1, o[8 * j + 7] * l1));
            }
            fence_async_smem();
            __syncwarp();
            if (lane == 0) mbar_arrive(ordy0 + (warp < 6 ? 0 : 8), 1);
        }
        const uint32_t stage = wg == 0 ? sbase + X4_OFF : slot0 + 4 * SLOT_BYTES + (wg - 1) * XCH_BYTES;
#pragma unroll
        for (int jt = 0; jt < 3; jt++) {
            const int j = jt * 3 + wg, s = j & 3;
            float acc[48];
            mbar_wait(full0 + 8 * s, (1 + (j >> 2)) & 1);
            const uint64_t da = make_desc(slot0 + s * SLOT_BYTES, 16);
            const uint64_t db = make_desc(sbase, 16);
            if (jt == 0) mbar_wait(ordy0, 0);
            token_wait(wg);
            wg_fence();
#pragma unroll
            for (int k = 0; k < 8; k++) wgmma_n96_ss_ta(acc, da + k * 128, db + ((k >> 2) * QHALF + (k & 3) * 32) / 16, k != 0);
            if (jt == 0) {
                mbar_wait(ordy0 + 8, 0);
                wg_fence();
            }
#pragma unroll
            for (int k = 0; k < 8; k++) {
                wgmma_n96_ss_ta(acc, da + (8 + k) * 128, db + (SQ * 128 + (k >> 2) * QHALF + (k & 3) * 32) / 16, 1);
                if (k == SPLIT_O - 1) wg_commit();
            }
            wg_commit();
            wg_wait<1>();
            if (j != NOT - 1) token_pass(wg);
            if (jt > 0) mbar_wait(sfree0 + 8 * wg, (jt - 1) & 1);
            wg_wait<0>();
            reg_fence(acc);
            if (lane == 0) mbar_arrive(empty0 + 8 * s, 3);
            store_tile_t<false>(acc, stage, wq, lane);
            fence_async_smem();
            __syncwarp();
            if (lane == 0) mbar_arrive(sfull0 + 8 * wg, 1);
        }
    }
}

typedef CUresult (*EncodeFn)(CUtensorMap*, CUtensorMapDataType, cuuint32_t, void*, const cuuint64_t*, const cuuint64_t*,
                             const cuuint32_t*, const cuuint32_t*, CUtensorMapInterleave, CUtensorMapSwizzle,
                             CUtensorMapL2promotion, CUtensorMapFloatOOBfill);

void encode(EncodeFn fn, CUtensorMap* tm, const void* ptr, int rank, const cuuint64_t* dims, const cuuint64_t* strides,
            const cuuint32_t* box, CUtensorMapL2promotion prom) {
    const cuuint32_t es[3] = {1, 1, 1};
    fn(tm, CU_TENSOR_MAP_DATA_TYPE_BFLOAT16, rank, const_cast<void*>(ptr), dims, strides, box, es,
       CU_TENSOR_MAP_INTERLEAVE_NONE, CU_TENSOR_MAP_SWIZZLE_128B, prom,
       CU_TENSOR_MAP_FLOAT_OOB_FILL_NONE);
}

}

extern "C" void kernel_launch(void* const* d_in, const int* in_sizes, int n_in, void* d_out, int out_size) {
    (void)in_sizes; (void)n_in; (void)out_size;
    static EncodeFn fn = nullptr;
    static int sms = 0;
    if (!fn) {
        void* p = nullptr;
        cudaDriverEntryPointQueryResult qr;
        cudaGetDriverEntryPoint("cuTensorMapEncodeTiled", &p, cudaEnableDefault, &qr);
        fn = (EncodeFn)p;
        int dev = 0;
        cudaGetDevice(&dev);
        cudaDeviceGetAttribute(&sms, cudaDevAttrMultiProcessorCount, dev);
        cudaFuncSetAttribute(gqa_fused_kernel, cudaFuncAttributeMaxDynamicSharedMemorySize, SMEM_BYTES);
    }
    CUtensorMap tx, twq, tk, tv, two, tout;
    {
        const cuuint64_t d[2] = {DM, NB * SQ}, s[1] = {DM * 2};
        const cuuint32_t bx[2] = {64, SQ};
        encode(fn, &tx, d_in[0], 2, d, s, bx, CU_TENSOR_MAP_L2_PROMOTION_L2_128B);
        encode(fn, &tout, d_out, 2, d, s, bx, CU_TENSOR_MAP_L2_PROMOTION_NONE);
    }
    {
        const cuuint64_t d[3] = {64, (cuuint64_t)NB * HKV * SK, 2}, s[2] = {DH * 2, 128};
        const cuuint32_t bx[3] = {64, 128, 2};
        encode(fn, &tk, d_in[1], 3, d, s, bx, CU_TENSOR_MAP_L2_PROMOTION_L2_256B);
        encode(fn, &tv, d_in[2], 3, d, s, bx, CU_TENSOR_MAP_L2_PROMOTION_L2_256B);
    }
    {
        const cuuint64_t d[3] = {64, DM, HQ * DH / 64}, s[2] = {HQ * DH * 2, 128};
        const cuuint32_t bx[3] = {64, 64, 4};
        encode(fn, &twq, d_in[3], 3, d, s, bx, CU_TENSOR_MAP_L2_PROMOTION_NONE);
    }
    {
        const cuuint64_t d[2] = {DM, HQ * DH}, s[1] = {DM * 2};
        const cuuint32_t bx[2] = {64, 256};
        encode(fn, &two, d_in[4], 2, d, s, bx, CU_TENSOR_MAP_L2_PROMOTION_L2_128B);
    }
    const int clear_in_kernel = sms >= NCTA;
    if (!clear_in_kernel) cudaMemsetAsync(d_out, 0, (size_t)NB * SQ * DM * 2, cudaStreamPerThread);
    const int grid = (XTRA && sms >= NCTA + 4) ? NCTA + 4 : NCTA;
    gqa_fused_kernel<<<grid, NTHREADS, SMEM_BYTES, cudaStreamPerThread>>>(
        tx, twq, tk, tv, two, tout, (__nv_bfloat16*)d_out, (const uint8_t*)d_in[0], (const uint8_t*)d_in[3],
        (const uint8_t*)d_in[1], (const uint8_t*)d_in[2], clear_in_kernel);
}
```

```cpp
#include <cuda_runtime.h>
#include <cuda_bf16.h>
#include <cuda.h>
#include <stdint.h>
#include <limits.h>

namespace {

constexpr int TOUCH_N = 7;
constexpr int TOUCH_D0 = 1000;
constexpr int TOUCH_DT = 560;
constexpr int XTRA = 3;
constexpr int XTRA_T0 = 1500;
constexpr int CAP = 2;
constexpr int PACE_A = 6850;
constexpr int PACE_T = 1290;
constexpr int ZERO_I = 12;
constexpr int SPLIT = 5;
constexpr int SPLIT_O = 4;
constexpr int PVA = 6;

constexpr int NB = 8, SQ = 96, DM = 576, HQ = 32, HKV = 16, SK = 1024, DH = 128;
constexpr int NCTA = NB * HKV;
constexpr int NSLOT = 5;
constexpr uint32_t SLOT_BYTES = 32768;
constexpr uint32_t QO_BYTES = 49152;
constexpr uint32_t QHALF = 24576;
constexpr uint32_t XCH_BYTES = 12288;
constexpr uint32_t X4_OFF = QO_BYTES + NSLOT * SLOT_BYTES;
constexpr uint32_t BAR_OFF = X4_OFF + XCH_BYTES;
constexpr uint32_t TSTART_OFF = BAR_OFF + 192;
constexpr uint32_t DUMMY_OFF = BAR_OFF + 256;
constexpr uint32_t SMEM_BYTES = BAR_OFF + 384 + 1024;
constexpr int NTHREADS = 512;
constexpr float QSCALE = 0.08838834764831845f * 1.4426950408889634f;
constexpr int NKT = SK / 128;
constexpr int NQC = DM / 64;
constexpr int NOT = DM / 64;

__device__ unsigned g_cnt[NB * 32];

__device__ __forceinline__ uint32_t smem_u32(const void* p) { return (uint32_t)__cvta_generic_to_shared(p); }
__device__ __forceinline__ long long global_ns() {
    long long t;
    asm volatile("mov.u64 %0, %globaltimer;" : "=l"(t)::"memory");
    return t;
}
__device__ __forceinline__ void wait_until_ns(long long due) {
    for (int it = 0; it < (1 << 16) && global_ns() < due; it++) {}
}
__device__ __forceinline__ void mbar_init(uint32_t bar, uint32_t cnt) {
    asm volatile("mbarrier.init.shared::cta.b64 [%0], %1;" ::"r"(bar), "r"(cnt) : "memory");
}
__device__ __forceinline__ void mbar_expect_tx(uint32_t bar, uint32_t bytes) {
    asm volatile("mbarrier.arrive.expect_tx.shared::cta.b64 _, [%0], %1;" ::"r"(bar), "r"(bytes) : "memory");
}
__device__ __forceinline__ void mbar_arrive(uint32_t bar, uint32_t cnt) {
    asm volatile("mbarrier.arrive.shared::cta.b64 _, [%0], %1;" ::"r"(bar), "r"(cnt) : "memory");
}
__device__ __forceinline__ void mbar_wait(uint32_t bar, uint32_t parity) {
    uint32_t ok;
    int it = 0;
    do {
        asm volatile("{\n.reg .pred p;\nmbarrier.try_wait.parity.shared::cta.b64 p, [%1], %2;\nselp.u32 %0, 1, 0, p;\n}"
                     : "=r"(ok) : "r"(bar), "r"(parity) : "memory");
        if (++it > (1 << 20)) break;
    } while (!ok);
}
__device__ __forceinline__ void tma_2d(uint32_t dst, const CUtensorMap* tm, int c0, int c1, uint32_t bar) {
    asm volatile("cp.async.bulk.tensor.2d.shared::cluster.global.mbarrier::complete_tx::bytes [%0], [%1, {%3, %4}], [%2];"
                 ::"r"(dst), "l"(tm), "r"(bar), "r"(c0), "r"(c1) : "memory");
}
__device__ __forceinline__ void tma_3d(uint32_t dst, const CUtensorMap* tm, int c0, int c1, int c2, uint32_t bar) {
    asm volatile("cp.async.bulk.tensor.3d.shared::cluster.global.mbarrier::complete_tx::bytes [%0], [%1, {%3, %4, %5}], [%2];"
                 ::"r"(dst), "l"(tm), "r"(bar), "r"(c0), "r"(c1), "r"(c2) : "memory");
}
__device__ __forceinline__ void prefetch_tm(const CUtensorMap* tm) { asm volatile("prefetch.tensormap [%0];" ::"l"(tm) : "memory"); }
__device__ __forceinline__ void prefetch_l2(const void* p) { asm volatile("prefetch.global.L2 [%0];" ::"l"(p)); }
__device__ __forceinline__ void wg_fence() { asm volatile("wgmma.fence.sync.aligned;" ::: "memory"); }
__device__ __forceinline__ void wg_commit() { asm volatile("wgmma.commit_group.sync.aligned;" ::: "memory"); }
template <int N> __device__ __forceinline__ void wg_wait() { asm volatile("wgmma.wait_group.sync.aligned %0;" ::"n"(N) : "memory"); }
template <int N> __device__ __forceinline__ void reg_fence(float (&d)[N]) {
#pragma unroll
    for (int i = 0; i < N; i++) asm volatile("" : "+f"(d[i])::"memory");
}
__device__ __forceinline__ void bar_consumers() { asm volatile("bar.sync 1, 384;" ::: "memory"); }
__device__ __forceinline__ void token_wait(int wg) { asm volatile("bar.sync %0, 256;" ::"r"(2 + wg) : "memory"); }
__device__ __forceinline__ void token_pass(int wg) { asm volatile("bar.arrive %0, 256;" ::"r"(wg == 2 ? 2 : 3 + wg) : "memory"); }
__device__ __forceinline__ void fence_async_smem() { asm volatile("fence.proxy.async.shared::cta;" ::: "memory"); }
__device__ __forceinline__ uint32_t pack_bf16(float lo, float hi) {
    uint32_t r;
    asm("cvt.rn.bf16x2.f32 %0, %1, %2;" : "=r"(r) : "f"(hi), "f"(lo));
    return r;
}
__device__ __forceinline__ float ex2(float x) {
    float y;
    asm("ex2.approx.ftz.f32 %0, %1;" : "=f"(y) : "f"(x));
    return y;
}
__device__ __forceinline__ void stsm_x4(uint32_t a, uint32_t r0, uint32_t r1, uint32_t r2, uint32_t r3) {
    asm volatile("stmatrix.sync.aligned.m8n8.x4.shared.b16 [%0], {%1, %2, %3, %4};" ::"r"(a), "r"(r0), "r"(r1), "r"(r2), "r"(r3) : "memory");
}
__device__ __forceinline__ void stsm_x4_t(uint32_t a, uint32_t r0, uint32_t r1, uint32_t r2, uint32_t r3) {
    asm volatile("stmatrix.sync.aligned.m8n8.x4.trans.shared.b16 [%0], {%1, %2, %3, %4};" ::"r"(a), "r"(r0), "r"(r1), "r"(r2), "r"(r3) : "memory");
}
__device__ __forceinline__ uint64_t make_desc(uint32_t addr, uint32_t lbo_bytes) {
    return (uint64_t)((addr & 0x3FFFF) >> 4) | ((uint64_t)(lbo_bytes >> 4) << 16) | ((uint64_t)64 << 32) | ((uint64_t)1 << 62);
}

__device__ __forceinline__ void wgmma_n96_ss_ta(float (&d)[48], uint64_t da, uint64_t db, int scale_d) {
    asm volatile("{\n.reg .pred p;\nsetp.ne.b32 p, %50, 0;\n"
        "wgmma.mma_async.sync.aligned.m64n96k16.f32.bf16.bf16 "
        "{%0, %1, %2, %3, %4, %5, %6, %7, %8, %9, %10, %11, %12, %13, %14, %15, "
        "%16, %17, %18, %19, %20, %21, %22, %23, %24, %25, %26, %27, %28, %29, %30, %31, "
        "%32, %33, %34, %35, %36, %37, %38, %39, %40, %41, %42, %43, %44, %45, %46, %47}, "
        "%48, %49, p, 1, 1, 1, 0;\n}\n"
        : "+f"(d[0]), "+f"(d[1]), "+f"(d[2]), "+f"(d[3]), "+f"(d[4]), "+f"(d[5]), "+f"(d[6]), "+f"(d[7]),
          "+f"(d[8]), "+f"(d[9]), "+f"(d[10]), "+f"(d[11]), "+f"(d[12]), "+f"(d[13]), "+f"(d[14]), "+f"(d[15]),
          "+f"(d[16]), "+f"(d[17]), "+f"(d[18]), "+f"(d[19]), "+f"(d[20]), "+f"(d[21]), "+f"(d[22]), "+f"(d[23]),
          "+f"(d[24]), "+f"(d[25]), "+f"(d[26]), "+f"(d[27]), "+f"(d[28]), "+f"(d[29]), "+f"(d[30]), "+f"(d[31]),
          "+f"(d[32]), "+f"(d[33]), "+f"(d[34]), "+f"(d[35]), "+f"(d[36]), "+f"(d[37]), "+f"(d[38]), "+f"(d[39]),
          "+f"(d[40]), "+f"(d[41]), "+f"(d[42]), "+f"(d[43]), "+f"(d[44]), "+f"(d[45]), "+f"(d[46]), "+f"(d[47])
        : "l"(da), "l"(db), "r"(scale_d));
}
__device__ __forceinline__ void wgmma_n128_ss(float (&d)[64], uint64_t da, uint64_t db, int scale_d) {
    asm volatile("{\n.reg .pred p;\nsetp.ne.b32 p, %66, 0;\n"
        "wgmma.mma_async.sync.aligned.m64n128k16.f32.bf16.bf16 "
        "{%0, %1, %2, %3, %4, %5, %6, %7, %8, %9, %10, %11, %12, %13, %14, %15, "
        "%16, %17, %18, %19, %20, %21, %22, %23, %24, %25, %26, %27, %28, %29, %30, %31, "
        "%32, %33, %34, %35, %36, %37, %38, %39, %40, %41, %42, %43, %44, %45, %46, %47, "
        "%48, %49, %50, %51, %52, %53, %54, %55, %56, %57, %58, %59, %60, %61, %62, %63}, "
        "%64, %65, p, 1, 1, 0, 0;\n}\n"
        : "+f"(d[0]), "+f"(d[1]), "+f"(d[2]), "+f"(d[3]), "+f"(d[4]), "+f"(d[5]), "+f"(d[6]), "+f"(d[7]),
          "+f"(d[8]), "+f"(d[9]), "+f"(d[10]), "+f"(d[11]), "+f"(d[12]), "+f"(d[13]), "+f"(d[14]), "+f"(d[15]),
          "+f"(d[16]), "+f"(d[17]), "+f"(d[18]), "+f"(d[19]), "+f"(d[20]), "+f"(d[21]), "+f"(d[22]), "+f"(d[23]),
          "+f"(d[24]), "+f"(d[25]), "+f"(d[26]), "+f"(d[27]), "+f"(d[28]), "+f"(d[29]), "+f"(d[30]), "+f"(d[31]),
          "+f"(d[32]), "+f"(d[33]), "+f"(d[34]), "+f"(d[35]), "+f"(d[36]), "+f"(d[37]), "+f"(d[38]), "+f"(d[39]),
          "+f"(d[40]), "+f"(d[41]), "+f"(d[42]), "+f"(d[43]), "+f"(d[44]), "+f"(d[45]), "+f"(d[46]), "+f"(d[47]),
          "+f"(d[48]), "+f"(d[49]), "+f"(d[50]), "+f"(d[51]), "+f"(d[52]), "+f"(d[53]), "+f"(d[54]), "+f"(d[55]),
          "+f"(d[56]), "+f"(d[57]), "+f"(d[58]), "+f"(d[59]), "+f"(d[60]), "+f"(d[61]), "+f"(d[62]), "+f"(d[63])
        : "l"(da), "l"(db), "r"(scale_d));
}
__device__ __forceinline__ void wgmma_n128_rs_tb(float (&d)[64], uint32_t a0, uint32_t a1, uint32_t a2, uint32_t a3, uint64_t db, int scale_d) {
    asm volatile("{\n.reg .pred p;\nsetp.ne.b32 p, %69, 0;\n"
        "wgmma.mma_async.sync.aligned.m64n128k16.f32.bf16.bf16 "
        "{%0, %1, %2, %3, %4, %5, %6, %7, %8, %9, %10, %11, %12, %13, %14, %15, "
        "%16, %17, %18, %19, %20, %21, %22, %23, %24, %25, %26, %27, %28, %29, %30, %31, "
        "%32, %33, %34, %35, %36, %37, %38, %39, %40, %41, %42, %43, %44, %45, %46, %47, "
        "%48, %49, %50, %51, %52, %53, %54, %55, %56, %57, %58, %59, %60, %61, %62, %63}, "
        "{%64, %65, %66, %67}, %68, p, 1, 1, 1;\n}\n"
        : "+f"(d[0]), "+f"(d[1]), "+f"(d[2]), "+f"(d[3]), "+f"(d[4]), "+f"(d[5]), "+f"(d[6]), "+f"(d[7]),
          "+f"(d[8]), "+f"(d[9]), "+f"(d[10]), "+f"(d[11]), "+f"(d[12]), "+f"(d[13]), "+f"(d[14]), "+f"(d[15]),
          "+f"(d[16]), "+f"(d[17]), "+f"(d[18]), "+f"(d[19]), "+f"(d[20]), "+f"(d[21]), "+f"(d[22]), "+f"(d[23]),
          "+f"(d[24]), "+f"(d[25]), "+f"(d[26]), "+f"(d[27]), "+f"(d[28]), "+f"(d[29]), "+f"(d[30]), "+f"(d[31]),
          "+f"(d[32]), "+f"(d[33]), "+f"(d[34]), "+f"(d[35]), "+f"(d[36]), "+f"(d[37]), "+f"(d[38]), "+f"(d[39]),
          "+f"(d[40]), "+f"(d[41]), "+f"(d[42]), "+f"(d[43]), "+f"(d[44]), "+f"(d[45]), "+f"(d[46]), "+f"(d[47]),
          "+f"(d[48]), "+f"(d[49]), "+f"(d[50]), "+f"(d[51]), "+f"(d[52]), "+f"(d[53]), "+f"(d[54]), "+f"(d[55]),
          "+f"(d[56]), "+f"(d[57]), "+f"(d[58]), "+f"(d[59]), "+f"(d[60]), "+f"(d[61]), "+f"(d[62]), "+f"(d[63])
        : "r"(a0), "r"(a1), "r"(a2), "r"(a3), "l"(db), "r"(scale_d));
}

template <bool SCALE>
__device__ __forceinline__ void store_tile_t(float (&acc)[48], uint32_t base, int wq, int lane) {
    if (SCALE) {
#pragma unroll
        for (int i = 0; i < 48; i++) acc[i] *= QSCALE;
    }
    const int mat = lane >> 3, r = lane & 7;
    const uint32_t a = base + (uint32_t)((mat >> 1) * 8 + r) * 128 + (uint32_t)((2 * wq + (mat & 1)) ^ r) * 16;
#pragma unroll
    for (int s = 0; s < 6; s++)
        stsm_x4_t(a + s * 16 * 128, pack_bf16(acc[8 * s + 0], acc[8 * s + 1]), pack_bf16(acc[8 * s + 2], acc[8 * s + 3]),
                  pack_bf16(acc[8 * s + 4], acc[8 * s + 5]), pack_bf16(acc[8 * s + 6], acc[8 * s + 7]));
}

__device__ __forceinline__ constexpr uint32_t x_off(int j) { return (j == 4 || j == NQC - 1) ? X4_OFF : (j % NSLOT) * XCH_BYTES; }

template <bool TWO>
__device__ __forceinline__ void qproj(uint32_t sbase, uint32_t qrdy, int wg, int wq, int lane) {
    const uint32_t slot0 = sbase + QO_BYTES;
    const uint32_t full0 = sbase + BAR_OFF, empty0 = full0 + 8 * NSLOT;
    float acc0[48], acc1[48];
#pragma unroll
    for (int j = 0; j < NQC; j++) {
        const int s = j % NSLOT;
        mbar_wait(full0 + 8 * s, (j / NSLOT) & 1);
        const uint64_t da = make_desc(slot0 + s * SLOT_BYTES + wg * 8192, 16);
        const uint64_t db = make_desc(sbase + x_off(j), 16);
        wg_fence();
        wgmma_n96_ss_ta(acc0, da, db, j != 0);
        if (TWO) wgmma_n96_ss_ta(acc1, da + 512, db, j != 0);
        wg_commit();
        if (j > 0) {
            wg_wait<1>();
            if (lane == 0) mbar_arrive(empty0 + 8 * ((j - 1) % NSLOT), 1);
        }
#pragma unroll
        for (int k = 1; k < 4; k++) {
            wgmma_n96_ss_ta(acc0, da + k * 128, db + k * 2, 1);
            if (TWO) wgmma_n96_ss_ta(acc1, da + 512 + k * 128, db + k * 2, 1);
        }
        wg_commit();
        bar_consumers();
    }
    wg_wait<0>();
    reg_fence(acc0);
    if (TWO) reg_fence(acc1);
    if (lane == 0) mbar_arrive(empty0 + 8 * ((NQC - 1) % NSLOT), 1);
    store_tile_t<true>(acc0, sbase + (wg & 1) * QHALF + (wg >> 1) * (SQ * 128), wq, lane);
    if (TWO) store_tile_t<true>(acc1, sbase + QHALF + SQ * 128, wq, lane);
    fence_async_smem();
    __syncwarp();
    if (lane == 0) mbar_arrive(qrdy, 1);
}

__global__ void __launch_bounds__(NTHREADS, 1)
gqa_fused_kernel(const __grid_constant__ CUtensorMap tm_x, const __grid_constant__ CUtensorMap tm_wq,
                 const __grid_constant__ CUtensorMap tm_k, const __grid_constant__ CUtensorMap tm_v,
                 const __grid_constant__ CUtensorMap tm_wo, const __grid_constant__ CUtensorMap tm_out,
                 __nv_bfloat16* __restrict__ out, const uint8_t* __restrict__ x_raw, const uint8_t* __restrict__ wq_raw,
                 const uint8_t* __restrict__ k_raw, const uint8_t* __restrict__ v_raw, int clear_out) {
    extern __shared__ __align__(1024) uint8_t smem_raw[];
    const uint32_t sbase = (smem_u32(smem_raw) + 1023u) & ~1023u;
    const uint32_t slot0 = sbase + QO_BYTES;
    const uint32_t full0 = sbase + BAR_OFF, empty0 = full0 + 8 * NSLOT;
    const uint32_t qrdy0 = full0 + 80, ordy0 = full0 + 96, sfull0 = full0 + 112, sfree0 = full0 + 136, zgo = full0 + 160;
    const int tid = threadIdx.x, lane = tid & 31;
    const int warp = __shfl_sync(0xffffffffu, tid >> 5, 0), wg = warp >> 2, wq = warp & 3;

    if (blockIdx.x >= NCTA) {
        wait_until_ns(global_ns() + XTRA_T0);
        for (int i = tid; i < XTRA * 32 * 64; i += NTHREADS) {
            const int piece = TOUCH_N + (i >> 11), item = (blockIdx.x - NCTA) * 32 + ((i >> 6) & 31), line = i & 63;
            prefetch_l2(((piece & 4) ? v_raw : k_raw) + (size_t)item * (SK * DH * 2) + (piece >> 3) * SLOT_BYTES + (piece & 3) * 8192 + line * 128);
        }
        return;
    }
    const int b = blockIdx.x & 7, kvh = blockIdx.x >> 3;

    if (tid == 384) {
        prefetch_tm(&tm_wq); prefetch_tm(&tm_x);
#pragma unroll
        for (int i = 0; i < NSLOT; i++) mbar_init(full0 + 8 * i, 1);
        asm volatile("fence.mbarrier_init.release.cluster;" ::: "memory");
#pragma unroll
        for (int j = 0; j < NSLOT; j++) {
            const uint32_t bar = full0 + 8 * j;
            mbar_expect_tx(bar, SLOT_BYTES + XCH_BYTES);
            tma_3d(slot0 + j * SLOT_BYTES, &tm_wq, 0, j * 64, kvh * 4, bar);
            tma_2d(sbase + x_off(j), &tm_x, j * 64, b * SQ, bar);
        }
    }
    if (tid == 448) {
#pragma unroll
        for (int i = 0; i < NSLOT; i++) mbar_init(empty0 + 8 * i, 12);
        mbar_init(qrdy0, 8); mbar_init(qrdy0 + 8, 4); mbar_init(ordy0, 6); mbar_init(ordy0 + 8, 6); mbar_init(zgo, 1);
#pragma unroll
        for (int i = 0; i < 3; i++) { mbar_init(sfull0 + 8 * i, 4); mbar_init(sfree0 + 8 * i, 1); }
    }
    if (tid == 480) asm volatile("st.shared.b64 [%0], %1;" ::"r"(sbase + TSTART_OFF), "l"(global_ns()) : "memory");
    __syncthreads();

    if (wg == 3) {
        asm volatile("setmaxnreg.dec.sync.aligned.u32 32;");
        if (warp == 12) {
            const int kvrow = (b * HKV + kvh) * SK;
            long long tstart;
            asm volatile("ld.shared.b64 %0, [%1];" : "=l"(tstart) : "r"(sbase + TSTART_OFF) : "memory");
            int s = 0, ph = 0;
            for (int g = NSLOT; g < NQC + 2 * NKT; g++) {
                const uint32_t bar = full0 + 8 * s;
                const int i = g - NQC;
                mbar_wait(empty0 + 8 * s, ph);
                if (i >= 3) {
                    mbar_wait(full0 + 8 * ((g - CAP) % NSLOT), ((g - CAP) / NSLOT) & 1);
                    const long long due = tstart + PACE_A + (long long)PACE_T * (i - 4);
                    wait_until_ns(due);
                }
                if (lane == 0) {
                    if (i < 0) {
                        mbar_expect_tx(bar, SLOT_BYTES + XCH_BYTES);
                        tma_3d(slot0 + s * SLOT_BYTES, &tm_wq, 0, g * 64, kvh * 4, bar);
                        if (g < NQC - 1) tma_2d(sbase + x_off(g), &tm_x, g * 64, b * SQ, bar);
                    } else {
                        if (i == 0) tma_2d(sbase + X4_OFF, &tm_x, (NQC - 1) * 64, b * SQ, full0 + 8 * ((NQC - 1) % NSLOT));
                        mbar_expect_tx(bar, SLOT_BYTES);
                        tma_3d(slot0 + s * SLOT_BYTES, (i & 1) ? &tm_v : &tm_k, 0, kvrow + (i >> 1) * 128, 0, bar);
                        if (i == ZERO_I) mbar_arrive(zgo, 1);
                    }
                }
                if (++s == NSLOT) { s = 0; ph ^= 1; }
            }
            mbar_wait(full0 + 8 * 4, 0);
            for (int j = 0; j < NOT; j++) {
                const uint32_t bar = full0 + 8 * (j & 3);
                mbar_wait(empty0 + 8 * (j & 3), (j >> 2) & 1);
                if (lane == 0) {
                    mbar_expect_tx(bar, SLOT_BYTES);
                    tma_2d(slot0 + (j & 3) * SLOT_BYTES, &tm_wo, ((j + kvh) % NOT) * 64, kvh * 256, bar);
                }
            }
        } else if (warp == 13) {
            mbar_wait(full0, 0);
            if (lane == 0) { prefetch_tm(&tm_k); prefetch_tm(&tm_v); prefetch_tm(&tm_wo); prefetch_tm(&tm_out); }
#pragma unroll
            for (int i = lane; i < (NQC - NSLOT) * 32; i += 32)
                prefetch_l2(wq_raw + (size_t)(NSLOT * 64 + (i >> 2) * 8 + b) * (HQ * DH * 2) + kvh * 512 + (i & 3) * 128);
            if (lane < (NQC - NSLOT) * 6) prefetch_l2(x_raw + (size_t)(b * SQ + kvh * 6 + lane % 6) * (DM * 2) + (NSLOT + lane / 6) * 128);
            const size_t kvoff = (size_t)(b * HKV + kvh) * SK * DH * 2;
            const long long t0 = clock64();
            for (int i = 0; i < TOUCH_N; i++) {
                while (clock64() - t0 < TOUCH_D0 + i * TOUCH_DT) {}
                const uint8_t* pp = ((i & 4) ? v_raw : k_raw) + kvoff + (size_t)(i >> 3) * SLOT_BYTES + (i & 3) * 8192 + lane * 32;
#pragma unroll
                for (int o = 0; o < 8; o++)
                    asm volatile("cp.async.ca.shared.global [%0], [%1], 4;" ::"r"(sbase + DUMMY_OFF + lane * 4), "l"(pp + o * 1024) : "memory");
            }
            asm volatile("cp.async.wait_all;" ::: "memory");
        } else if (warp == 14) {
            if (clear_out) {
                mbar_wait(zgo, 0);
                uint4* z = reinterpret_cast<uint4*>(out + (size_t)(b * SQ + kvh * 6) * DM);
                for (int i = lane; i < 6 * DM * 2 / 16; i += 32) z[i] = make_uint4(0, 0, 0, 0);
                asm volatile("fence.proxy.async.global;" ::: "memory");
                __syncwarp();
                if (lane == 0) {
                    __threadfence();
                    const unsigned target = (atomicAdd(&g_cnt[b * 32], 1u) / HKV + 1) * HKV;
                    for (int it = 0; it < (1 << 16); it++) {
                        unsigned v;
                        asm volatile("ld.acquire.gpu.global.u32 %0, [%1];" : "=r"(v) : "l"(&g_cnt[b * 32]) : "memory");
                        if ((int)(v - target) >= 0) break;
                        __nanosleep(200);
                    }
                    asm volatile("fence.proxy.async.global;" ::: "memory");
                }
            }
            if (lane == 0) {
                for (int j = 0, w = 0; j < NOT; j++) {
                    mbar_wait(sfull0 + 8 * w, (j / 3) & 1);
                    const uint32_t stage = w == 0 ? sbase + X4_OFF : slot0 + 4 * SLOT_BYTES + (w - 1) * XCH_BYTES;
                    asm volatile("cp.reduce.async.bulk.tensor.2d.global.shared::cta.add.tile.bulk_group [%0, {%2, %3}], [%1];"
                                 ::"l"(&tm_out), "r"(stage), "r"(((j + kvh) % NOT) * 64), "r"(b * SQ) : "memory");
                    asm volatile("cp.async.bulk.commit_group;" ::: "memory");
                    if (j >= 1 && j <= 6) {
                        asm volatile("cp.async.bulk.wait_group.read 1;" ::: "memory");
                        mbar_arrive(sfree0 + 8 * (w == 0 ? 2 : w - 1), 1);
                    }
                    if (++w == 3) w = 0;
                }
                asm volatile("cp.async.bulk.wait_group.read 0;" ::: "memory");
            }
        }
    } else {
        asm volatile("setmaxnreg.inc.sync.aligned.u32 160;");
        if (wg == 2) qproj<true>(sbase, qrdy0 + 8, wg, wq, lane);
        else qproj<false>(sbase, qrdy0, wg, wq, lane);
        if (wg == 2) token_pass(2);
        if (wg < 2) mbar_wait(qrdy0, 0);
        if (wg > 0) mbar_wait(qrdy0 + 8, 0);
        float o[64];
#pragma unroll
        for (int j = 0; j < 64; j++) o[j] = 0.f;
        float m0 = -INFINITY, m1 = -INFINITY, l0 = 0.f, l1 = 0.f;
        bool zero_ref = false;
        const uint64_t dq = make_desc(sbase + wg * 8192, 16);
        int slot = NQC % NSLOT;
        uint32_t phase = (NQC / NSLOT) & 1;
#pragma unroll 1
        for (int t = 0; t < NKT; t++) {
            float s[64];
            {
                mbar_wait(full0 + 8 * slot, phase);
                const uint64_t dk = make_desc(slot0 + slot * SLOT_BYTES, 16);
                token_wait(wg);
                wg_fence();
#pragma unroll
                for (int k = 0; k < 8; k++) {
                    wgmma_n128_ss(s, dq + (k >> 2) * (QHALF >> 4) + (k & 3) * 2, dk + (k >> 2) * 1024 + (k & 3) * 2, k != 0);
                    if (k == SPLIT - 1) wg_commit();
                }
                wg_commit();
                wg_wait<1>();
                token_pass(wg);
                wg_wait<0>();
                reg_fence(s);
                if (lane == 0) mbar_arrive(empty0 + 8 * slot, 1);
                if (++slot == NSLOT) { slot = 0; phase ^= 1; }
            }
            {
                int ia0 = max(__float_as_int(s[0]), __float_as_int(s[1])), ia1 = max(__float_as_int(s[2]), __float_as_int(s[3]));
                int ib0 = max(__float_as_int(s[4]), __float_as_int(s[5])), ib1 = max(__float_as_int(s[6]), __float_as_int(s[7]));
#pragma unroll
                for (int j = 1; j < 8; j++) {
                    ia0 = __vimax3_s32(ia0, __float_as_int(s[8 * j + 0]), __float_as_int(s[8 * j + 1]));
                    ia1 = __vimax3_s32(ia1, __float_as_int(s[8 * j + 2]), __float_as_int(s[8 * j + 3]));
                    ib0 = __vimax3_s32(ib0, __float_as_int(s[8 * j + 4]), __float_as_int(s[8 * j + 5]));
                    ib1 = __vimax3_s32(ib1, __float_as_int(s[8 * j + 6]), __float_as_int(s[8 * j + 7]));
                }
                const float th0 = m0 + 16.f, th1 = m1 + 16.f;
                const int ti0 = th0 >= 0.f ? __float_as_int(th0) : INT_MIN, ti1 = th1 >= 0.f ? __float_as_int(th1) : INT_MIN;
                if (__any_sync(0xffffffffu, max(ia0, ib0) >= ti0 || max(ia1, ib1) >= ti1)) {
                    float mx0 = m0, mx1 = m1;
#pragma unroll
                    for (int j = 0; j < 16; j++) {
                        mx0 = fmaxf(mx0, fmaxf(s[4 * j], s[4 * j + 1]));
                        mx1 = fmaxf(mx1, fmaxf(s[4 * j + 2], s[4 * j + 3]));
                    }
                    mx0 = fmaxf(mx0, __shfl_xor_sync(0xffffffffu, mx0, 1));
                    mx1 = fmaxf(mx1, __shfl_xor_sync(0xffffffffu, mx1, 1));
                    mx0 = fmaxf(mx0, __shfl_xor_sync(0xffffffffu, mx0, 2));
                    mx1 = fmaxf(mx1, __shfl_xor_sync(0xffffffffu, mx1, 2));
                    zero_ref = t == 0 && __all_sync(0xffffffffu, mx0 >= -40.f && mx0 < 16.f && mx1 >= -40.f && mx1 < 16.f);
                    if (zero_ref) { mx0 = 0.f; mx1 = 0.f; }
                    const float a0 = ex2(m0 - mx0), a1 = ex2(m1 - mx1);
                    m0 = mx0; m1 = mx1;
                    l0 *= a0; l1 *= a1;
#pragma unroll
                    for (int j = 0; j < 16; j++) { o[4 * j] *= a0; o[4 * j + 1] *= a0; o[4 * j + 2] *= a1; o[4 * j + 3] *= a1; }
                }
                if (!zero_ref) {
#pragma unroll
                    for (int j = 0; j < 16; j++) { s[4 * j] -= m0; s[4 * j + 1] -= m0; s[4 * j + 2] -= m1; s[4 * j + 3] -= m1; }
                }
            }
            uint32_t p[32];
            auto exp_block = [&](int j) {
                const float e0 = ex2(s[4 * j + 0]), e1 = ex2(s[4 * j + 1]), e2 = ex2(s[4 * j + 2]), e3 = ex2(s[4 * j + 3]);
                l0 += e0 + e1; l1 += e2 + e3;
                p[2 * j] = pack_bf16(e0, e1);
                p[2 * j + 1] = pack_bf16(e2, e3);
            };
#pragma unroll
            for (int j = 0; j < 2 * PVA; j++) exp_block(j);
            mbar_wait(full0 + 8 * slot, phase);
            const uint64_t dv = make_desc(slot0 + slot * SLOT_BYTES, 16384);
            token_wait(wg);
            wg_fence();
#pragma unroll
            for (int k = 0; k < PVA; k++) wgmma_n128_rs_tb(o, p[4 * k], p[4 * k + 1], p[4 * k + 2], p[4 * k + 3], dv + k * 128, 1);
            wg_commit();
            mbar_wait(full0 + 8 * slot, phase);
#pragma unroll
            for (int j = 2 * PVA; j < 16; j++) exp_block(j);
            wg_fence();
#pragma unroll
            for (int k = PVA; k < 8; k++) wgmma_n128_rs_tb(o, p[4 * k], p[4 * k + 1], p[4 * k + 2], p[4 * k + 3], dv + k * 128, 1);
            wg_commit();
            token_pass(wg);
            if (t == NKT - 1) {
                l0 += __shfl_xor_sync(0xffffffffu, l0, 1); l1 += __shfl_xor_sync(0xffffffffu, l1, 1);
                l0 += __shfl_xor_sync(0xffffffffu, l0, 2); l1 += __shfl_xor_sync(0xffffffffu, l1, 2);
                asm volatile("rcp.approx.ftz.f32 %0, %0;" : "+f"(l0));
                asm volatile("rcp.approx.ftz.f32 %0, %0;" : "+f"(l1));
            }
            wg_wait<0>();
            reg_fence(o);
            if (lane == 0) mbar_arrive(empty0 + 8 * slot, 1);
            if (++slot == NSLOT) { slot = 0; phase ^= 1; }
        }
        {
            const int mat = lane >> 3, r = lane & 7;
            const uint32_t rowaddr = sbase + (uint32_t)(wg * 64 + wq * 16 + (mat & 1) * 8 + r) * 128;
#pragma unroll
            for (int j = 0; j < 8; j++) {
                const uint32_t chunk = (uint32_t)(((2 * j + (mat >> 1)) & 7) ^ r);
                stsm_x4(rowaddr + (j >> 2) * QHALF + chunk * 16,
                        pack_bf16(o[8 * j + 0] * l0, o[8 * j + 1] * l0), pack_bf16(o[8 * j + 2] * l1, o[8 * j + 3] * l1),
                        pack_bf16(o[8 * j + 4] * l0, o[8 * j + 5] * l0), pack_bf16(o[8 * j + 6] * l1, o[8 * j + 7] * l1));
            }
            fence_async_smem();
            __syncwarp();
            if (lane == 0) mbar_arrive(ordy0 + (warp < 6 ? 0 : 8), 1);
        }
        const uint32_t stage = wg == 0 ? sbase + X4_OFF : slot0 + 4 * SLOT_BYTES + (wg - 1) * XCH_BYTES;
#pragma unroll
        for (int jt = 0; jt < 3; jt++) {
            const int j = jt * 3 + wg, s = j & 3;
            float acc[48];
            mbar_wait(full0 + 8 * s, (1 + (j >> 2)) & 1);
            const uint64_t da = make_desc(slot0 + s * SLOT_BYTES, 16);
            const uint64_t db = make_desc(sbase, 16);
            if (jt == 0) mbar_wait(ordy0, 0);
            token_wait(wg);
            wg_fence();
#pragma unroll
            for (int k = 0; k < 8; k++) wgmma_n96_ss_ta(acc, da + k * 128, db + ((k >> 2) * QHALF + (k & 3) * 32) / 16, k != 0);
            if (jt == 0) {
                mbar_wait(ordy0 + 8, 0);
                wg_fence();
            }
#pragma unroll
            for (int k = 0; k < 8; k++) {
                wgmma_n96_ss_ta(acc, da + (8 + k) * 128, db + (SQ * 128 + (k >> 2) * QHALF + (k & 3) * 32) / 16, 1);
                if (k == SPLIT_O - 1) wg_commit();
            }
            wg_commit();
            wg_wait<1>();
            if (j != NOT - 1) token_pass(wg);
            if (jt > 0) mbar_wait(sfree0 + 8 * wg, (jt - 1) & 1);
            wg_wait<0>();
            reg_fence(acc);
            if (lane == 0) mbar_arrive(empty0 + 8 * s, 3);
            store_tile_t<false>(acc, stage, wq, lane);
            fence_async_smem();
            __syncwarp();
            if (lane == 0) mbar_arrive(sfull0 + 8 * wg, 1);
        }
    }
}

typedef CUresult (*EncodeFn)(CUtensorMap*, CUtensorMapDataType, cuuint32_t, void*, const cuuint64_t*, const cuuint64_t*,
                             const cuuint32_t*, const cuuint32_t*, CUtensorMapInterleave, CUtensorMapSwizzle,
                             CUtensorMapL2promotion, CUtensorMapFloatOOBfill);

void encode(EncodeFn fn, CUtensorMap* tm, const void* ptr, int rank, const cuuint64_t* dims, const cuuint64_t* strides,
            const cuuint32_t* box, CUtensorMapL2promotion prom) {
    const cuuint32_t es[3] = {1, 1, 1};
    fn(tm, CU_TENSOR_MAP_DATA_TYPE_BFLOAT16, rank, const_cast<void*>(ptr), dims, strides, box, es,
       CU_TENSOR_MAP_INTERLEAVE_NONE, CU_TENSOR_MAP_SWIZZLE_128B, prom,
       CU_TENSOR_MAP_FLOAT_OOB_FILL_NONE);
}

}

extern "C" void kernel_launch(void* const* d_in, const int* in_sizes, int n_in, void* d_out, int out_size) {
    (void)in_sizes; (void)n_in; (void)out_size;
    static EncodeFn fn = nullptr;
    static int sms = 0;
    if (!fn) {
        void* p = nullptr;
        cudaDriverEntryPointQueryResult qr;
        cudaGetDriverEntryPoint("cuTensorMapEncodeTiled", &p, cudaEnableDefault, &qr);
        fn = (EncodeFn)p;
        int dev = 0;
        cudaGetDevice(&dev);
        cudaDeviceGetAttribute(&sms, cudaDevAttrMultiProcessorCount, dev);
        cudaFuncSetAttribute(gqa_fused_kernel, cudaFuncAttributeMaxDynamicSharedMemorySize, SMEM_BYTES);
    }
    CUtensorMap tx, twq, tk, tv, two, tout;
    {
        const cuuint64_t d[2] = {DM, NB * SQ}, s[1] = {DM * 2};
        const cuuint32_t bx[2] = {64, SQ};
        encode(fn, &tx, d_in[0], 2, d, s, bx, CU_TENSOR_MAP_L2_PROMOTION_L2_128B);
        encode(fn, &tout, d_out, 2, d, s, bx, CU_TENSOR_MAP_L2_PROMOTION_NONE);
    }
    {
        const cuuint64_t d[3] = {64, (cuuint64_t)NB * HKV * SK, 2}, s[2] = {DH * 2, 128};
        const cuuint32_t bx[3] = {64, 128, 2};
        encode(fn, &tk, d_in[1], 3, d, s, bx, CU_TENSOR_MAP_L2_PROMOTION_L2_256B);
        encode(fn, &tv, d_in[2], 3, d, s, bx, CU_TENSOR_MAP_L2_PROMOTION_L2_256B);
    }
    {
        const cuuint64_t d[3] = {64, DM, HQ * DH / 64}, s[2] = {HQ * DH * 2, 128};
        const cuuint32_t bx[3] = {64, 64, 4};
        encode(fn, &twq, d_in[3], 3, d, s, bx, CU_TENSOR_MAP_L2_PROMOTION_NONE);
    }
    {
        const cuuint64_t d[2] = {DM, HQ * DH}, s[1] = {DM * 2};
        const cuuint32_t bx[2] = {64, 256};
        encode(fn, &two, d_in[4], 2, d, s, bx, CU_TENSOR_MAP_L2_PROMOTION_L2_128B);
    }
    const int clear_in_kernel = sms >= NCTA;
    if (!clear_in_kernel) cudaMemsetAsync(d_out, 0, (size_t)NB * SQ * DM * 2, cudaStreamPerThread);
    const int grid = (XTRA && sms >= NCTA + 4) ? NCTA + 4 : NCTA;
    gqa_fused_kernel<<<grid, NTHREADS, SMEM_BYTES, cudaStreamPerThread>>>(
        tx, twq, tk, tv, two, tout, (__nv_bfloat16*)d_out, (const uint8_t*)d_in[0], (const uint8_t*)d_in[3],
        (const uint8_t*)d_in[1], (const uint8_t*)d_in[2], clear_in_kernel);
}
```

```cpp
#include <cuda_runtime.h>
#include <cuda_bf16.h>
#include <cuda.h>
#include <stdint.h>
#include <limits.h>

namespace {

constexpr int TOUCH_N = 7;
constexpr int TOUCH_D0 = 1000;
constexpr int TOUCH_DT = 560;
constexpr int XTRA = 3;
constexpr int XTRA_T0 = 1500;
constexpr int CAP = 2;
constexpr int PACE_A = 6850;
constexpr int PACE_T = 1290;
constexpr int ZERO_I = 12;
constexpr int SPLIT = 5;
constexpr int SPLIT_O = 3;
constexpr int NPAUSE = 3;
constexpr int SKEW = 200;
constexpr int PVA = 6;

constexpr int NB = 8, SQ = 96, DM = 576, HQ = 32, HKV = 16, SK = 1024, DH = 128;
constexpr int NCTA = NB * HKV;
constexpr int NSLOT = 5;
constexpr uint32_t SLOT_BYTES = 32768;
constexpr uint32_t QO_BYTES = 49152;
constexpr uint32_t QHALF = 24576;
constexpr uint32_t XCH_BYTES = 12288;
constexpr uint32_t X4_OFF = QO_BYTES + NSLOT * SLOT_BYTES;
constexpr uint32_t BAR_OFF = X4_OFF + XCH_BYTES;
constexpr uint32_t TSTART_OFF = BAR_OFF + 192;
constexpr uint32_t DUMMY_OFF = BAR_OFF + 256;
constexpr uint32_t SMEM_BYTES = BAR_OFF + 384 + 1024;
constexpr int NTHREADS = 512;
constexpr float QSCALE = 0.08838834764831845f * 1.4426950408889634f;
constexpr int NKT = SK / 128;
constexpr int NQC = DM / 64;
constexpr int NOT = DM / 64;

__device__ unsigned g_cnt[NB * 32];

__device__ __forceinline__ uint32_t smem_u32(const void* p) { return (uint32_t)__cvta_generic_to_shared(p); }
__device__ __forceinline__ long long global_ns() {
    long long t;
    asm volatile("mov.u64 %0, %globaltimer;" : "=l"(t)::"memory");
    return t;
}
__device__ __forceinline__ void wait_until_ns(long long due) {
    for (int it = 0; it < (1 << 16) && global_ns() < due; it++) {}
}
__device__ __forceinline__ void mbar_init(uint32_t bar, uint32_t cnt) {
    asm volatile("mbarrier.init.shared::cta.b64 [%0], %1;" ::"r"(bar), "r"(cnt) : "memory");
}
__device__ __forceinline__ void mbar_expect_tx(uint32_t bar, uint32_t bytes) {
    asm volatile("mbarrier.arrive.expect_tx.shared::cta.b64 _, [%0], %1;" ::"r"(bar), "r"(bytes) : "memory");
}
__device__ __forceinline__ void mbar_arrive(uint32_t bar, uint32_t cnt) {
    asm volatile("mbarrier.arrive.shared::cta.b64 _, [%0], %1;" ::"r"(bar), "r"(cnt) : "memory");
}
__device__ __forceinline__ void mbar_wait(uint32_t bar, uint32_t parity) {
    uint32_t ok;
    int it = 0;
    do {
        asm volatile("{\n.reg .pred p;\nmbarrier.try_wait.parity.shared::cta.b64 p, [%1], %2;\nselp.u32 %0, 1, 0, p;\n}"
                     : "=r"(ok) : "r"(bar), "r"(parity) : "memory");
        if (++it > (1 << 20)) break;
    } while (!ok);
}
__device__ __forceinline__ void tma_2d(uint32_t dst, const CUtensorMap* tm, int c0, int c1, uint32_t bar) {
    asm volatile("cp.async.bulk.tensor.2d.shared::cluster.global.mbarrier::complete_tx::bytes [%0], [%1, {%3, %4}], [%2];"
                 ::"r"(dst), "l"(tm), "r"(bar), "r"(c0), "r"(c1) : "memory");
}
__device__ __forceinline__ void tma_3d(uint32_t dst, const CUtensorMap* tm, int c0, int c1, int c2, uint32_t bar) {
    asm volatile("cp.async.bulk.tensor.3d.shared::cluster.global.mbarrier::complete_tx::bytes [%0], [%1, {%3, %4, %5}], [%2];"
                 ::"r"(dst), "l"(tm), "r"(bar), "r"(c0), "r"(c1), "r"(c2) : "memory");
}
__device__ __forceinline__ void prefetch_tm(const CUtensorMap* tm) { asm volatile("prefetch.tensormap [%0];" ::"l"(tm) : "memory"); }
__device__ __forceinline__ void prefetch_l2(const void* p) { asm volatile("prefetch.global.L2 [%0];" ::"l"(p)); }
__device__ __forceinline__ void wg_fence() { asm volatile("wgmma.fence.sync.aligned;" ::: "memory"); }
__device__ __forceinline__ void wg_commit() { asm volatile("wgmma.commit_group.sync.aligned;" ::: "memory"); }
template <int N> __device__ __forceinline__ void wg_wait() { asm volatile("wgmma.wait_group.sync.aligned %0;" ::"n"(N) : "memory"); }
template <int N> __device__ __forceinline__ void reg_fence(float (&d)[N]) {
#pragma unroll
    for (int i = 0; i < N; i++) asm volatile("" : "+f"(d[i])::"memory");
}
__device__ __forceinline__ void bar_consumers() { asm volatile("bar.sync 1, 384;" ::: "memory"); }
__device__ __forceinline__ void token_wait(int wg) { asm volatile("bar.sync %0, 256;" ::"r"(2 + wg) : "memory"); }
__device__ __forceinline__ void token_pass(int wg) { asm volatile("bar.arrive %0, 256;" ::"r"(wg == 2 ? 2 : 3 + wg) : "memory"); }
__device__ __forceinline__ void fence_async_smem() { asm volatile("fence.proxy.async.shared::cta;" ::: "memory"); }
__device__ __forceinline__ uint32_t pack_bf16(float lo, float hi) {
    uint32_t r;
    asm("cvt.rn.bf16x2.f32 %0, %1, %2;" : "=r"(r) : "f"(hi), "f"(lo));
    return r;
}
__device__ __forceinline__ float ex2(float x) {
    float y;
    asm("ex2.approx.ftz.f32 %0, %1;" : "=f"(y) : "f"(x));
    return y;
}
__device__ __forceinline__ void stsm_x4(uint32_t a, uint32_t r0, uint32_t r1, uint32_t r2, uint32_t r3) {
    asm volatile("stmatrix.sync.aligned.m8n8.x4.shared.b16 [%0], {%1, %2, %3, %4};" ::"r"(a), "r"(r0), "r"(r1), "r"(r2), "r"(r3) : "memory");
}
__device__ __forceinline__ void stsm_x4_t(uint32_t a, uint32_t r0, uint32_t r1, uint32_t r2, uint32_t r3) {
    asm volatile("stmatrix.sync.aligned.m8n8.x4.trans.shared.b16 [%0], {%1, %2, %3, %4};" ::"r"(a), "r"(r0), "r"(r1), "r"(r2), "r"(r3) : "memory");
}
__device__ __forceinline__ uint64_t make_desc(uint32_t addr, uint32_t lbo_bytes) {
    return (uint64_t)((addr & 0x3FFFF) >> 4) | ((uint64_t)(lbo_bytes >> 4) << 16) | ((uint64_t)64 << 32) | ((uint64_t)1 << 62);
}

__device__ __forceinline__ void wgmma_n96_ss_ta(float (&d)[48], uint64_t da, uint64_t db, int scale_d) {
    asm volatile("{\n.reg .pred p;\nsetp.ne.b32 p, %50, 0;\n"
        "wgmma.mma_async.sync.aligned.m64n96k16.f32.bf16.bf16 "
        "{%0, %1, %2, %3, %4, %5, %6, %7, %8, %9, %10, %11, %12, %13, %14, %15, "
        "%16, %17, %18, %19, %20, %21, %22, %23, %24, %25, %26, %27, %28, %29, %30, %31, "
        "%32, %33, %34, %35, %36, %37, %38, %39, %40, %41, %42, %43, %44, %45, %46, %47}, "
        "%48, %49, p, 1, 1, 1, 0;\n}\n"
        : "+f"(d[0]), "+f"(d[1]), "+f"(d[2]), "+f"(d[3]), "+f"(d[4]), "+f"(d[5]), "+f"(d[6]), "+f"(d[7]),
          "+f"(d[8]), "+f"(d[9]), "+f"(d[10]), "+f"(d[11]), "+f"(d[12]), "+f"(d[13]), "+f"(d[14]), "+f"(d[15]),
          "+f"(d[16]), "+f"(d[17]), "+f"(d[18]), "+f"(d[19]), "+f"(d[20]), "+f"(d[21]), "+f"(d[22]), "+f"(d[23]),
          "+f"(d[24]), "+f"(d[25]), "+f"(d[26]), "+f"(d[27]), "+f"(d[28]), "+f"(d[29]), "+f"(d[30]), "+f"(d[31]),
          "+f"(d[32]), "+f"(d[33]), "+f"(d[34]), "+f"(d[35]), "+f"(d[36]), "+f"(d[37]), "+f"(d[38]), "+f"(d[39]),
          "+f"(d[40]), "+f"(d[41]), "+f"(d[42]), "+f"(d[43]), "+f"(d[44]), "+f"(d[45]), "+f"(d[46]), "+f"(d[47])
        : "l"(da), "l"(db), "r"(scale_d));
}
__device__ __forceinline__ void wgmma_n128_ss(float (&d)[64], uint64_t da, uint64_t db, int scale_d) {
    asm volatile("{\n.reg .pred p;\nsetp.ne.b32 p, %66, 0;\n"
        "wgmma.mma_async.sync.aligned.m64n128k16.f32.bf16.bf16 "
        "{%0, %1, %2, %3, %4, %5, %6, %7, %8, %9, %10, %11, %12, %13, %14, %15, "
        "%16, %17, %18, %19, %20, %21, %22, %23, %24, %25, %26, %27, %28, %29, %30, %31, "
        "%32, %33, %34, %35, %36, %37, %38, %39, %40, %41, %42, %43, %44, %45, %46, %47, "
        "%48, %49, %50, %51, %52, %53, %54, %55, %56, %57, %58, %59, %60, %61, %62, %63}, "
        "%64, %65, p, 1, 1, 0, 0;\n}\n"
        : "+f"(d[0]), "+f"(d[1]), "+f"(d[2]), "+f"(d[3]), "+f"(d[4]), "+f"(d[5]), "+f"(d[6]), "+f"(d[7]),
          "+f"(d[8]), "+f"(d[9]), "+f"(d[10]), "+f"(d[11]), "+f"(d[12]), "+f"(d[13]), "+f"(d[14]), "+f"(d[15]),
          "+f"(d[16]), "+f"(d[17]), "+f"(d[18]), "+f"(d[19]), "+f"(d[20]), "+f"(d[21]), "+f"(d[22]), "+f"(d[23]),
          "+f"(d[24]), "+f"(d[25]), "+f"(d[26]), "+f"(d[27]), "+f"(d[28]), "+f"(d[29]), "+f"(d[30]), "+f"(d[31]),
          "+f"(d[32]), "+f"(d[33]), "+f"(d[34]), "+f"(d[35]), "+f"(d[36]), "+f"(d[37]), "+f"(d[38]), "+f"(d[39]),
          "+f"(d[40]), "+f"(d[41]), "+f"(d[42]), "+f"(d[43]), "+f"(d[44]), "+f"(d[45]), "+f"(d[46]), "+f"(d[47]),
          "+f"(d[48]), "+f"(d[49]), "+f"(d[50]), "+f"(d[51]), "+f"(d[52]), "+f"(d[53]), "+f"(d[54]), "+f"(d[55]),
          "+f"(d[56]), "+f"(d[57]), "+f"(d[58]), "+f"(d[59]), "+f"(d[60]), "+f"(d[61]), "+f"(d[62]), "+f"(d[63])
        : "l"(da), "l"(db), "r"(scale_d));
}
__device__ __forceinline__ void wgmma_n128_rs_tb(float (&d)[64], uint32_t a0, uint32_t a1, uint32_t a2, uint32_t a3, uint64_t db, int scale_d) {
    asm volatile("{\n.reg .pred p;\nsetp.ne.b32 p, %69, 0;\n"
        "wgmma.mma_async.sync.aligned.m64n128k16.f32.bf16.bf16 "
        "{%0, %1, %2, %3, %4, %5, %6, %7, %8, %9, %10, %11, %12, %13, %14, %15, "
        "%16, %17, %18, %19, %20, %21, %22, %23, %24, %25, %26, %27, %28, %29, %30, %31, "
        "%32, %33, %34, %35, %36, %37, %38, %39, %40, %41, %42, %43, %44, %45, %46, %47, "
        "%48, %49, %50, %51, %52, %53, %54, %55, %56, %57, %58, %59, %60, %61, %62, %63}, "
        "{%64, %65, %66, %67}, %68, p, 1, 1, 1;\n}\n"
        : "+f"(d[0]), "+f"(d[1]), "+f"(d[2]), "+f"(d[3]), "+f"(d[4]), "+f"(d[5]), "+f"(d[6]), "+f"(d[7]),
          "+f"(d[8]), "+f"(d[9]), "+f"(d[10]), "+f"(d[11]), "+f"(d[12]), "+f"(d[13]), "+f"(d[14]), "+f"(d[15]),
          "+f"(d[16]), "+f"(d[17]), "+f"(d[18]), "+f"(d[19]), "+f"(d[20]), "+f"(d[21]), "+f"(d[22]), "+f"(d[23]),
          "+f"(d[24]), "+f"(d[25]), "+f"(d[26]), "+f"(d[27]), "+f"(d[28]), "+f"(d[29]), "+f"(d[30]), "+f"(d[31]),
          "+f"(d[32]), "+f"(d[33]), "+f"(d[34]), "+f"(d[35]), "+f"(d[36]), "+f"(d[37]), "+f"(d[38]), "+f"(d[39]),
          "+f"(d[40]), "+f"(d[41]), "+f"(d[42]), "+f"(d[43]), "+f"(d[44]), "+f"(d[45]), "+f"(d[46]), "+f"(d[47]),
          "+f"(d[48]), "+f"(d[49]), "+f"(d[50]), "+f"(d[51]), "+f"(d[52]), "+f"(d[53]), "+f"(d[54]), "+f"(d[55]),
          "+f"(d[56]), "+f"(d[57]), "+f"(d[58]), "+f"(d[59]), "+f"(d[60]), "+f"(d[61]), "+f"(d[62]), "+f"(d[63])
        : "r"(a0), "r"(a1), "r"(a2), "r"(a3), "l"(db), "r"(scale_d));
}

template <bool SCALE>
__device__ __forceinline__ void store_tile_t(float (&acc)[48], uint32_t base, int wq, int lane) {
    if (SCALE) {
#pragma unroll
        for (int i = 0; i < 48; i++) acc[i] *= QSCALE;
    }
    const int mat = lane >> 3, r = lane & 7;
    const uint32_t a = base + (uint32_t)((mat >> 1) * 8 + r) * 128 + (uint32_t)((2 * wq + (mat & 1)) ^ r) * 16;
#pragma unroll
    for (int s = 0; s < 6; s++)
        stsm_x4_t(a + s * 16 * 128, pack_bf16(acc[8 * s + 0], acc[8 * s + 1]), pack_bf16(acc[8 * s + 2], acc[8 * s + 3]),
                  pack_bf16(acc[8 * s + 4], acc[8 * s + 5]), pack_bf16(acc[8 * s + 6], acc[8 * s + 7]));
}

__device__ __forceinline__ constexpr uint32_t x_off(int j) { return (j == 4 || j == NQC - 1) ? X4_OFF : (j % NSLOT) * XCH_BYTES; }

template <bool TWO>
__device__ __forceinline__ void qproj(uint32_t sbase, uint32_t qrdy, int wg, int wq, int lane) {
    const uint32_t slot0 = sbase + QO_BYTES;
    const uint32_t full0 = sbase + BAR_OFF, empty0 = full0 + 8 * NSLOT;
    float acc0[48], acc1[48];
#pragma unroll
    for (int j = 0; j < NQC; j++) {
        const int s = j % NSLOT;
        mbar_wait(full0 + 8 * s, (j / NSLOT) & 1);
        const uint64_t da = make_desc(slot0 + s * SLOT_BYTES + wg * 8192, 16);
        const uint64_t db = make_desc(sbase + x_off(j), 16);
        wg_fence();
        wgmma_n96_ss_ta(acc0, da, db, j != 0);
        if (TWO) wgmma_n96_ss_ta(acc1, da + 512, db, j != 0);
        wg_commit();
        if (j > 0) {
            wg_wait<1>();
            if (lane == 0) mbar_arrive(empty0 + 8 * ((j - 1) % NSLOT), 1);
        }
#pragma unroll
        for (int k = 1; k < 4; k++) {
            wgmma_n96_ss_ta(acc0, da + k * 128, db + k * 2, 1);
            if (TWO) wgmma_n96_ss_ta(acc1, da + 512 + k * 128, db + k * 2, 1);
        }
        wg_commit();
        bar_consumers();
    }
    wg_wait<0>();
    reg_fence(acc0);
    if (TWO) reg_fence(acc1);
    if (lane == 0) mbar_arrive(empty0 + 8 * ((NQC - 1) % NSLOT), 1);
    store_tile_t<true>(acc0, sbase + (wg & 1) * QHALF + (wg >> 1) * (SQ * 128), wq, lane);
    if (TWO) store_tile_t<true>(acc1, sbase + QHALF + SQ * 128, wq, lane);
    fence_async_smem();
    __syncwarp();
    if (lane == 0) mbar_arrive(qrdy, 1);
}

__global__ void __launch_bounds__(NTHREADS, 1)
gqa_fused_kernel(const __grid_constant__ CUtensorMap tm_x, const __grid_constant__ CUtensorMap tm_wq,
                 const __grid_constant__ CUtensorMap tm_k, const __grid_constant__ CUtensorMap tm_v,
                 const __grid_constant__ CUtensorMap tm_wo, const __grid_constant__ CUtensorMap tm_out,
                 __nv_bfloat16* __restrict__ out, const uint8_t* __restrict__ x_raw, const uint8_t* __restrict__ wq_raw,
                 const uint8_t* __restrict__ k_raw, const uint8_t* __restrict__ v_raw, int clear_out) {
    extern __shared__ __align__(1024) uint8_t smem_raw[];
    const uint32_t sbase = (smem_u32(smem_raw) + 1023u) & ~1023u;
    const uint32_t slot0 = sbase + QO_BYTES;
    const uint32_t full0 = sbase + BAR_OFF, empty0 = full0 + 8 * NSLOT;
    const uint32_t qrdy0 = full0 + 80, ordy0 = full0 + 96, sfull0 = full0 + 112, sfree0 = full0 + 136, zgo = full0 + 160;
    const int tid = threadIdx.x, lane = tid & 31;
    const int warp = __shfl_sync(0xffffffffu, tid >> 5, 0), wg = warp >> 2, wq = warp & 3;

    if (blockIdx.x >= NCTA) {
        wait_until_ns(global_ns() + XTRA_T0);
        for (int i = tid; i < XTRA * 32 * 64; i += NTHREADS) {
            const int piece = TOUCH_N + (i >> 11), item = (blockIdx.x - NCTA) * 32 + ((i >> 6) & 31), line = i & 63;
            prefetch_l2(((piece & 4) ? v_raw : k_raw) + (size_t)item * (SK * DH * 2) + (piece >> 3) * SLOT_BYTES + (piece & 3) * 8192 + line * 128);
        }
        return;
    }
    const int b = blockIdx.x & 7, kvh = blockIdx.x >> 3;

    if (tid == 384) {
        prefetch_tm(&tm_wq); prefetch_tm(&tm_x);
#pragma unroll
        for (int i = 0; i < NSLOT; i++) mbar_init(full0 + 8 * i, 1);
        asm volatile("fence.mbarrier_init.release.cluster;" ::: "memory");
#pragma unroll
        for (int j = 0; j < NSLOT; j++) {
            const uint32_t bar = full0 + 8 * j;
            mbar_expect_tx(bar, SLOT_BYTES + XCH_BYTES);
            tma_3d(slot0 + j * SLOT_BYTES, &tm_wq, 0, j * 64, kvh * 4, bar);
            tma_2d(sbase + x_off(j), &tm_x, j * 64, b * SQ, bar);
        }
    }
    if (tid == 448) {
#pragma unroll
        for (int i = 0; i < NSLOT; i++) mbar_init(empty0 + 8 * i, 12);
        mbar_init(qrdy0, 8); mbar_init(qrdy0 + 8, 4); mbar_init(ordy0, 6); mbar_init(ordy0 + 8, 6); mbar_init(zgo, 1);
#pragma unroll
        for (int i = 0; i < 3; i++) { mbar_init(sfull0 + 8 * i, 4); mbar_init(sfree0 + 8 * i, 1); }
    }
    if (tid == 480) asm volatile("st.shared.b64 [%0], %1;" ::"r"(sbase + TSTART_OFF), "l"(global_ns()) : "memory");
    __syncthreads();

    if (wg == 3) {
        asm volatile("setmaxnreg.dec.sync.aligned.u32 32;");
        if (warp == 12) {
            const int kvrow = (b * HKV + kvh) * SK;
            long long tstart;
            asm volatile("ld.shared.b64 %0, [%1];" : "=l"(tstart) : "r"(sbase + TSTART_OFF) : "memory");
            int s = 0, ph = 0;
            for (int g = NSLOT; g < NQC + 2 * NKT; g++) {
                const uint32_t bar = full0 + 8 * s;
                const int i = g - NQC;
                mbar_wait(empty0 + 8 * s, ph);
                if (i >= 3) {
                    mbar_wait(full0 + 8 * ((g - CAP) % NSLOT), ((g - CAP) / NSLOT) & 1);
                    const long long due = tstart + PACE_A + PACE_T * (i - 4) + ((b & 1) ? SKEW : -SKEW) * (i - 3) / 12;
                    wait_until_ns(due);
                }
                if (lane == 0) {
                    if (i < 0) {
                        mbar_expect_tx(bar, SLOT_BYTES + XCH_BYTES);
                        tma_3d(slot0 + s * SLOT_BYTES, &tm_wq, 0, g * 64, kvh * 4, bar);
                        if (g < NQC - 1) tma_2d(sbase + x_off(g), &tm_x, g * 64, b * SQ, bar);
                    } else {
                        if (i == 0) tma_2d(sbase + X4_OFF, &tm_x, (NQC - 1) * 64, b * SQ, full0 + 8 * ((NQC - 1) % NSLOT));
                        mbar_expect_tx(bar, SLOT_BYTES);
                        tma_3d(slot0 + s * SLOT_BYTES, (i & 1) ? &tm_v : &tm_k, 0, kvrow + (i >> 1) * 128, 0, bar);
                        if (i == ZERO_I) mbar_arrive(zgo, 1);
                    }
                }
                if (++s == NSLOT) { s = 0; ph ^= 1; }
            }
            mbar_wait(full0 + 8 * 4, 0);
            for (int j = 0; j < NOT; j++) {
                const uint32_t bar = full0 + 8 * (j & 3);
                mbar_wait(empty0 + 8 * (j & 3), (j >> 2) & 1);
                if (lane == 0) {
                    mbar_expect_tx(bar, SLOT_BYTES);
                    tma_2d(slot0 + (j & 3) * SLOT_BYTES, &tm_wo, ((j + kvh) % NOT) * 64, kvh * 256, bar);
                }
            }
        } else if (warp == 13) {
            mbar_wait(full0, 0);
            if (lane == 0) { prefetch_tm(&tm_k); prefetch_tm(&tm_v); prefetch_tm(&tm_wo); prefetch_tm(&tm_out); }
#pragma unroll
            for (int i = lane; i < (NQC - NSLOT) * 32; i += 32)
                prefetch_l2(wq_raw + (size_t)(NSLOT * 64 + (i >> 2) * 8 + b) * (HQ * DH * 2) + kvh * 512 + (i & 3) * 128);
            if (lane < (NQC - NSLOT) * 6) prefetch_l2(x_raw + (size_t)(b * SQ + kvh * 6 + lane % 6) * (DM * 2) + (NSLOT + lane / 6) * 128);
            const size_t kvoff = (size_t)(b * HKV + kvh) * SK * DH * 2;
            const long long t0 = clock64();
            for (int i = 0; i < TOUCH_N; i++) {
                while (clock64() - t0 < TOUCH_D0 + i * TOUCH_DT) {}
                const uint8_t* pp = ((i & 4) ? v_raw : k_raw) + kvoff + (size_t)(i >> 3) * SLOT_BYTES + (i & 3) * 8192 + lane * 32;
#pragma unroll
                for (int o = 0; o < 8; o++)
                    asm volatile("cp.async.ca.shared.global [%0], [%1], 4;" ::"r"(sbase + DUMMY_OFF + lane * 4), "l"(pp + o * 1024) : "memory");
            }
            asm volatile("cp.async.wait_all;" ::: "memory");
        } else if (warp == 14) {
            if (clear_out) {
                mbar_wait(zgo, 0);
                uint4* z = reinterpret_cast<uint4*>(out + (size_t)(b * SQ + kvh * 6) * DM);
                for (int i = lane; i < 6 * DM * 2 / 16; i += 32) z[i] = make_uint4(0, 0, 0, 0);
                asm volatile("fence.proxy.async.global;" ::: "memory");
                __syncwarp();
                if (lane == 0) {
                    __threadfence();
                    const unsigned target = (atomicAdd(&g_cnt[b * 32], 1u) / HKV + 1) * HKV;
                    for (int it = 0; it < (1 << 16); it++) {
                        unsigned v;
                        asm volatile("ld.acquire.gpu.global.u32 %0, [%1];" : "=r"(v) : "l"(&g_cnt[b * 32]) : "memory");
                        if ((int)(v - target) >= 0) break;
                        __nanosleep(200);
                    }
                    asm volatile("fence.proxy.async.global;" ::: "memory");
                }
            }
            if (lane == 0) {
                for (int j = 0, w = 0; j < NOT; j++) {
                    mbar_wait(sfull0 + 8 * w, (j / 3) & 1);
                    const uint32_t stage = w == 0 ? sbase + X4_OFF : slot0 + 4 * SLOT_BYTES + (w - 1) * XCH_BYTES;
                    asm volatile("cp.reduce.async.bulk.tensor.2d.global.shared::cta.add.tile.bulk_group [%0, {%2, %3}], [%1];"
                                 ::"l"(&tm_out), "r"(stage), "r"(((j + kvh) % NOT) * 64), "r"(b * SQ) : "memory");
                    asm volatile("cp.async.bulk.commit_group;" ::: "memory");
                    if (j >= 1 && j <= 6) {
                        asm volatile("cp.async.bulk.wait_group.read 1;" ::: "memory");
                        mbar_arrive(sfree0 + 8 * (w == 0 ? 2 : w - 1), 1);
                    }
                    if (++w == 3) w = 0;
                }
                asm volatile("cp.async.bulk.wait_group.read 0;" ::: "memory");
            }
        }
    } else {
        asm volatile("setmaxnreg.inc.sync.aligned.u32 160;");
        if (wg == 2) qproj<true>(sbase, qrdy0 + 8, wg, wq, lane);
        else qproj<false>(sbase, qrdy0, wg, wq, lane);
        if (wg == 2) token_pass(2);
        if (wg < 2) mbar_wait(qrdy0, 0);
        if (wg > 0) mbar_wait(qrdy0 + 8, 0);
        float o[64];
#pragma unroll
        for (int j = 0; j < 64; j++) o[j] = 0.f;
        float m0 = -INFINITY, m1 = -INFINITY, l0 = 0.f, l1 = 0.f;
        bool zero_ref = false;
        const uint64_t dq = make_desc(sbase + wg * 8192, 16);
        int slot = NQC % NSLOT;
        uint32_t phase = (NQC / NSLOT) & 1;
#pragma unroll 1
        for (int t = 0; t < NKT; t++) {
            float s[64];
            {
                mbar_wait(full0 + 8 * slot, phase);
                const uint64_t dk = make_desc(slot0 + slot * SLOT_BYTES, 16);
                token_wait(wg);
                wg_fence();
#pragma unroll
                for (int k = 0; k < 8; k++) {
                    wgmma_n128_ss(s, dq + (k >> 2) * (QHALF >> 4) + (k & 3) * 2, dk + (k >> 2) * 1024 + (k & 3) * 2, k != 0);
                    if (k == SPLIT - 1) wg_commit();
                }
                wg_commit();
                wg_wait<1>();
                token_pass(wg);
                wg_wait<0>();
                reg_fence(s);
                if (lane == 0) mbar_arrive(empty0 + 8 * slot, 1);
                if (++slot == NSLOT) { slot = 0; phase ^= 1; }
            }
            {
                int ia0 = max(__float_as_int(s[0]), __float_as_int(s[1])), ia1 = max(__float_as_int(s[2]), __float_as_int(s[3]));
                int ib0 = max(__float_as_int(s[4]), __float_as_int(s[5])), ib1 = max(__float_as_int(s[6]), __float_as_int(s[7]));
#pragma unroll
                for (int j = 1; j < 8; j++) {
                    ia0 = __vimax3_s32(ia0, __float_as_int(s[8 * j + 0]), __float_as_int(s[8 * j + 1]));
                    ia1 = __vimax3_s32(ia1, __float_as_int(s[8 * j + 2]), __float_as_int(s[8 * j + 3]));
                    ib0 = __vimax3_s32(ib0, __float_as_int(s[8 * j + 4]), __float_as_int(s[8 * j + 5]));
                    ib1 = __vimax3_s32(ib1, __float_as_int(s[8 * j + 6]), __float_as_int(s[8 * j + 7]));
                }
                const float th0 = m0 + 16.f, th1 = m1 + 16.f;
                const int ti0 = th0 >= 0.f ? __float_as_int(th0) : INT_MIN, ti1 = th1 >= 0.f ? __float_as_int(th1) : INT_MIN;
                if (__any_sync(0xffffffffu, max(ia0, ib0) >= ti0 || max(ia1, ib1) >= ti1)) {
                    float mx0 = m0, mx1 = m1;
#pragma unroll
                    for (int j = 0; j < 16; j++) {
                        mx0 = fmaxf(mx0, fmaxf(s[4 * j], s[4 * j + 1]));
                        mx1 = fmaxf(mx1, fmaxf(s[4 * j + 2], s[4 * j + 3]));
                    }
                    mx0 = fmaxf(mx0, __shfl_xor_sync(0xffffffffu, mx0, 1));
                    mx1 = fmaxf(mx1, __shfl_xor_sync(0xffffffffu, mx1, 1));
                    mx0 = fmaxf(mx0, __shfl_xor_sync(0xffffffffu, mx0, 2));
                    mx1 = fmaxf(mx1, __shfl_xor_sync(0xffffffffu, mx1, 2));
                    zero_ref = t == 0 && __all_sync(0xffffffffu, mx0 >= -40.f && mx0 < 16.f && mx1 >= -40.f && mx1 < 16.f);
                    if (zero_ref) { mx0 = 0.f; mx1 = 0.f; }
                    const float a0 = ex2(m0 - mx0), a1 = ex2(m1 - mx1);
                    m0 = mx0; m1 = mx1;
                    l0 *= a0; l1 *= a1;
#pragma unroll
                    for (int j = 0; j < 16; j++) { o[4 * j] *= a0; o[4 * j + 1] *= a0; o[4 * j + 2] *= a1; o[4 * j + 3] *= a1; }
                }
                if (!zero_ref) {
#pragma unroll
                    for (int j = 0; j < 16; j++) { s[4 * j] -= m0; s[4 * j + 1] -= m0; s[4 * j + 2] -= m1; s[4 * j + 3] -= m1; }
                }
            }
            uint32_t p[32];
            auto exp_block = [&](int j) {
                const float e0 = ex2(s[4 * j + 0]), e1 = ex2(s[4 * j + 1]), e2 = ex2(s[4 * j + 2]), e3 = ex2(s[4 * j + 3]);
                l0 += e0 + e1; l1 += e2 + e3;
                p[2 * j] = pack_bf16(e0, e1);
                p[2 * j + 1] = pack_bf16(e2, e3);
            };
#pragma unroll
            for (int j = 0; j < 2 * PVA; j++) exp_block(j);
            mbar_wait(full0 + 8 * slot, phase);
            const uint64_t dv = make_desc(slot0 + slot * SLOT_BYTES, 16384);
            token_wait(wg);
            wg_fence();
#pragma unroll
            for (int k = 0; k < PVA; k++) wgmma_n128_rs_tb(o, p[4 * k], p[4 * k + 1], p[4 * k + 2], p[4 * k + 3], dv + k * 128, 1);
            wg_commit();
            mbar_wait(full0 + 8 * slot, phase);
#pragma unroll
            for (int j = 2 * PVA; j < 16; j++) exp_block(j);
            wg_fence();
#pragma unroll
            for (int k = PVA; k < 8; k++) wgmma_n128_rs_tb(o, p[4 * k], p[4 * k + 1], p[4 * k + 2], p[4 * k + 3], dv + k * 128, 1);
            wg_commit();
            token_pass(wg);
            if (t == NKT - 1) {
                l0 += __shfl_xor_sync(0xffffffffu, l0, 1); l1 += __shfl_xor_sync(0xffffffffu, l1, 1);
                l0 += __shfl_xor_sync(0xffffffffu, l0, 2); l1 += __shfl_xor_sync(0xffffffffu, l1, 2);
                asm volatile("rcp.approx.ftz.f32 %0, %0;" : "+f"(l0));
                asm volatile("rcp.approx.ftz.f32 %0, %0;" : "+f"(l1));
            }
            wg_wait<0>();
            reg_fence(o);
            if (lane == 0) mbar_arrive(empty0 + 8 * slot, 1);
            if (++slot == NSLOT) { slot = 0; phase ^= 1; }
        }
        {
            const int mat = lane >> 3, r = lane & 7;
            const uint32_t rowaddr = sbase + (uint32_t)(wg * 64 + wq * 16 + (mat & 1) * 8 + r) * 128;
#pragma unroll
            for (int j = 0; j < 8; j++) {
                const uint32_t chunk = (uint32_t)(((2 * j + (mat >> 1)) & 7) ^ r);
                stsm_x4(rowaddr + (j >> 2) * QHALF + chunk * 16,
                        pack_bf16(o[8 * j + 0] * l0, o[8 * j + 1] * l0), pack_bf16(o[8 * j + 2] * l1, o[8 * j + 3] * l1),
                        pack_bf16(o[8 * j + 4] * l0, o[8 * j + 5] * l0), pack_bf16(o[8 * j + 6] * l1, o[8 * j + 7] * l1));
            }
            fence_async_smem();
            __syncwarp();
            if (lane == 0) mbar_arrive(ordy0 + (warp < 6 ? 0 : 8), 1);
        }
        const uint32_t stage = wg == 0 ? sbase + X4_OFF : slot0 + 4 * SLOT_BYTES + (wg - 1) * XCH_BYTES;
#pragma unroll
        for (int jt = 0; jt < 3; jt++) {
            const int j = jt * 3 + wg, s = j & 3;
            float acc[48];
            mbar_wait(full0 + 8 * s, (1 + (j >> 2)) & 1);
            const uint64_t da = make_desc(slot0 + s * SLOT_BYTES, 16);
            const uint64_t db = make_desc(sbase, 16);
            if (jt == 0) mbar_wait(ordy0, 0);
            token_wait(wg);
            wg_fence();
#pragma unroll
            for (int k = 0; k < 8; k++) wgmma_n96_ss_ta(acc, da + k * 128, db + ((k >> 2) * QHALF + (k & 3) * 32) / 16, k != 0);
            if (jt == 0) {
                mbar_wait(ordy0 + 8, 0);
                wg_fence();
            }
#pragma unroll
            for (int k = 0; k < 8; k++) {
                wgmma_n96_ss_ta(acc, da + (8 + k) * 128, db + (SQ * 128 + (k >> 2) * QHALF + (k & 3) * 32) / 16, 1);
                if (k == SPLIT_O - 1) wg_commit();
            }
            wg_commit();
            wg_wait<1>();
            if (j >= NPAUSE && j != NOT - 1) token_pass(wg);
            if (jt > 0) mbar_wait(sfree0 + 8 * wg, (jt - 1) & 1);
            wg_wait<0>();
            reg_fence(acc);
            if (lane == 0) mbar_arrive(empty0 + 8 * s, 3);
            store_tile_t<false>(acc, stage, wq, lane);
            if (j < NPAUSE) token_pass(wg);
            fence_async_smem();
            __syncwarp();
            if (lane == 0) mbar_arrive(sfull0 + 8 * wg, 1);
        }
    }
}

typedef CUresult (*EncodeFn)(CUtensorMap*, CUtensorMapDataType, cuuint32_t, void*, const cuuint64_t*, const cuuint64_t*,
                             const cuuint32_t*, const cuuint32_t*, CUtensorMapInterleave, CUtensorMapSwizzle,
                             CUtensorMapL2promotion, CUtensorMapFloatOOBfill);

void encode(EncodeFn fn, CUtensorMap* tm, const void* ptr, int rank, const cuuint64_t* dims, const cuuint64_t* strides,
            const cuuint32_t* box, CUtensorMapL2promotion prom) {
    const cuuint32_t es[3] = {1, 1, 1};
    fn(tm, CU_TENSOR_MAP_DATA_TYPE_BFLOAT16, rank, const_cast<void*>(ptr), dims, strides, box, es,
       CU_TENSOR_MAP_INTERLEAVE_NONE, CU_TENSOR_MAP_SWIZZLE_128B, prom,
       CU_TENSOR_MAP_FLOAT_OOB_FILL_NONE);
}

}

extern "C" void kernel_launch(void* const* d_in, const int* in_sizes, int n_in, void* d_out, int out_size) {
    (void)in_sizes; (void)n_in; (void)out_size;
    static EncodeFn fn = nullptr;
    static int sms = 0;
    if (!fn) {
        void* p = nullptr;
        cudaDriverEntryPointQueryResult qr;
        cudaGetDriverEntryPoint("cuTensorMapEncodeTiled", &p, cudaEnableDefault, &qr);
        fn = (EncodeFn)p;
        int dev = 0;
        cudaGetDevice(&dev);
        cudaDeviceGetAttribute(&sms, cudaDevAttrMultiProcessorCount, dev);
        cudaFuncSetAttribute(gqa_fused_kernel, cudaFuncAttributeMaxDynamicSharedMemorySize, SMEM_BYTES);
    }
    CUtensorMap tx, twq, tk, tv, two, tout;
    {
        const cuuint64_t d[2] = {DM, NB * SQ}, s[1] = {DM * 2};
        const cuuint32_t bx[2] = {64, SQ};
        encode(fn, &tx, d_in[0], 2, d, s, bx, CU_TENSOR_MAP_L2_PROMOTION_L2_128B);
        encode(fn, &tout, d_out, 2, d, s, bx, CU_TENSOR_MAP_L2_PROMOTION_NONE);
    }
    {
        const cuuint64_t d[3] = {64, (cuuint64_t)NB * HKV * SK, 2}, s[2] = {DH * 2, 128};
        const cuuint32_t bx[3] = {64, 128, 2};
        encode(fn, &tk, d_in[1], 3, d, s, bx, CU_TENSOR_MAP_L2_PROMOTION_L2_256B);
        encode(fn, &tv, d_in[2], 3, d, s, bx, CU_TENSOR_MAP_L2_PROMOTION_L2_256B);
    }
    {
        const cuuint64_t d[3] = {64, DM, HQ * DH / 64}, s[2] = {HQ * DH * 2, 128};
        const cuuint32_t bx[3] = {64, 64, 4};
        encode(fn, &twq, d_in[3], 3, d, s, bx, CU_TENSOR_MAP_L2_PROMOTION_NONE);
    }
    {
        const cuuint64_t d[2] = {DM, HQ * DH}, s[1] = {DM * 2};
        const cuuint32_t bx[2] = {64, 256};
        encode(fn, &two, d_in[4], 2, d, s, bx, CU_TENSOR_MAP_L2_PROMOTION_L2_128B);
    }
    const int clear_in_kernel = sms >= NCTA;
    if (!clear_in_kernel) cudaMemsetAsync(d_out, 0, (size_t)NB * SQ * DM * 2, cudaStreamPerThread);
    const int grid = (XTRA && sms >= NCTA + 4) ? NCTA + 4 : NCTA;
    gqa_fused_kernel<<<grid, NTHREADS, SMEM_BYTES, cudaStreamPerThread>>>(
        tx, twq, tk, tv, two, tout, (__nv_bfloat16*)d_out, (const uint8_t*)d_in[0], (const uint8_t*)d_in[3],
        (const uint8_t*)d_in[1], (const uint8_t*)d_in[2], clear_in_kernel);
}
```

```cpp
#include <cuda_runtime.h>
#include <cuda_bf16.h>
#include <cuda.h>
#include <stdint.h>
#include <limits.h>

namespace {

constexpr int TOUCH_N = 7;
constexpr int TOUCH_D0 = 1000;
constexpr int TOUCH_DT = 560;
constexpr int XTRA = 3;
constexpr int XTRA_T0 = 1500;
constexpr int CAP = 2;
constexpr int PACE_A = 6850;
constexpr int PACE_T = 1290;
constexpr int ZERO_I = 12;
constexpr int SPLIT = 5;
constexpr int SPLIT_O = 3;
constexpr int SKEW = 200;
constexpr int GATE = 100;
constexpr int VLATE = 300;
constexpr int PVA = 6;

constexpr int NB = 8, SQ = 96, DM = 576, HQ = 32, HKV = 16, SK = 1024, DH = 128;
constexpr int NCTA = NB * HKV;
constexpr int NSLOT = 5;
constexpr uint32_t SLOT_BYTES = 32768;
constexpr uint32_t QO_BYTES = 49152;
constexpr uint32_t QHALF = 24576;
constexpr uint32_t XCH_BYTES = 12288;
constexpr uint32_t X4_OFF = QO_BYTES + NSLOT * SLOT_BYTES;
constexpr uint32_t BAR_OFF = X4_OFF + XCH_BYTES;
constexpr uint32_t TSTART_OFF = BAR_OFF + 240;
constexpr uint32_t PEER_OFF = QO_BYTES;
constexpr uint32_t STAGE2_OFF = PEER_OFF + QO_BYTES;
constexpr uint32_t DUMMY_OFF = BAR_OFF + 256;
constexpr uint32_t SMEM_BYTES = BAR_OFF + 384 + 1024;
constexpr int NTHREADS = 512;
constexpr float QSCALE = 0.08838834764831845f * 1.4426950408889634f;
constexpr int NKT = SK / 128;
constexpr int NQC = DM / 64;
constexpr int NOT = DM / 64;

__device__ unsigned g_cnt[NB * 32];

__device__ __forceinline__ uint32_t smem_u32(const void* p) { return (uint32_t)__cvta_generic_to_shared(p); }
__device__ __forceinline__ long long global_ns() {
    long long t;
    asm volatile("mov.u64 %0, %globaltimer;" : "=l"(t)::"memory");
    return t;
}
__device__ __forceinline__ void wait_until_ns(long long due) {
    for (int it = 0; it < (1 << 16) && global_ns() < due; it++) {}
}
__device__ __forceinline__ void mbar_init(uint32_t bar, uint32_t cnt) {
    asm volatile("mbarrier.init.shared::cta.b64 [%0], %1;" ::"r"(bar), "r"(cnt) : "memory");
}
__device__ __forceinline__ void mbar_expect_tx(uint32_t bar, uint32_t bytes) {
    asm volatile("mbarrier.arrive.expect_tx.shared::cta.b64 _, [%0], %1;" ::"r"(bar), "r"(bytes) : "memory");
}
__device__ __forceinline__ void mbar_arrive(uint32_t bar, uint32_t cnt) {
    asm volatile("mbarrier.arrive.shared::cta.b64 _, [%0], %1;" ::"r"(bar), "r"(cnt) : "memory");
}
__device__ __forceinline__ void mbar_wait(uint32_t bar, uint32_t parity) {
    uint32_t ok;
    int it = 0;
    do {
        asm volatile("{\n.reg .pred p;\nmbarrier.try_wait.parity.shared::cta.b64 p, [%1], %2;\nselp.u32 %0, 1, 0, p;\n}"
                     : "=r"(ok) : "r"(bar), "r"(parity) : "memory");
        if (++it > (1 << 20)) break;
    } while (!ok);
}
__device__ __forceinline__ void tma_2d(uint32_t dst, const CUtensorMap* tm, int c0, int c1, uint32_t bar) {
    asm volatile("cp.async.bulk.tensor.2d.shared::cluster.global.mbarrier::complete_tx::bytes [%0], [%1, {%3, %4}], [%2];"
                 ::"r"(dst), "l"(tm), "r"(bar), "r"(c0), "r"(c1) : "memory");
}
__device__ __forceinline__ void tma_3d(uint32_t dst, const CUtensorMap* tm, int c0, int c1, int c2, uint32_t bar) {
    asm volatile("cp.async.bulk.tensor.3d.shared::cluster.global.mbarrier::complete_tx::bytes [%0], [%1, {%3, %4, %5}], [%2];"
                 ::"r"(dst), "l"(tm), "r"(bar), "r"(c0), "r"(c1), "r"(c2) : "memory");
}
__device__ __forceinline__ void prefetch_tm(const CUtensorMap* tm) { asm volatile("prefetch.tensormap [%0];" ::"l"(tm) : "memory"); }
__device__ __forceinline__ void prefetch_l2(const void* p) { asm volatile("prefetch.global.L2 [%0];" ::"l"(p)); }
__device__ __forceinline__ void wg_fence() { asm volatile("wgmma.fence.sync.aligned;" ::: "memory"); }
__device__ __forceinline__ void wg_commit() { asm volatile("wgmma.commit_group.sync.aligned;" ::: "memory"); }
template <int N> __device__ __forceinline__ void wg_wait() { asm volatile("wgmma.wait_group.sync.aligned %0;" ::"n"(N) : "memory"); }
template <int N> __device__ __forceinline__ void reg_fence(float (&d)[N]) {
#pragma unroll
    for (int i = 0; i < N; i++) asm volatile("" : "+f"(d[i])::"memory");
}
__device__ __forceinline__ void bar_consumers() { asm volatile("bar.sync 1, 384;" ::: "memory"); }
__device__ __forceinline__ void token_wait(int wg) { asm volatile("bar.sync %0, 256;" ::"r"(2 + wg) : "memory"); }
__device__ __forceinline__ void token_pass(int wg) { asm volatile("bar.arrive %0, 256;" ::"r"(wg == 2 ? 2 : 3 + wg) : "memory"); }
__device__ __forceinline__ void fence_async_smem() { asm volatile("fence.proxy.async.shared::cta;" ::: "memory"); }
__device__ __forceinline__ uint32_t pack_bf16(float lo, float hi) {
    uint32_t r;
    asm("cvt.rn.bf16x2.f32 %0, %1, %2;" : "=r"(r) : "f"(hi), "f"(lo));
    return r;
}
__device__ __forceinline__ float ex2(float x) {
    float y;
    asm("ex2.approx.ftz.f32 %0, %1;" : "=f"(y) : "f"(x));
    return y;
}
__device__ __forceinline__ void stsm_x4(uint32_t a, uint32_t r0, uint32_t r1, uint32_t r2, uint32_t r3) {
    asm volatile("stmatrix.sync.aligned.m8n8.x4.shared.b16 [%0], {%1, %2, %3, %4};" ::"r"(a), "r"(r0), "r"(r1), "r"(r2), "r"(r3) : "memory");
}
__device__ __forceinline__ void stsm_x4_t(uint32_t a, uint32_t r0, uint32_t r1, uint32_t r2, uint32_t r3) {
    asm volatile("stmatrix.sync.aligned.m8n8.x4.trans.shared.b16 [%0], {%1, %2, %3, %4};" ::"r"(a), "r"(r0), "r"(r1), "r"(r2), "r"(r3) : "memory");
}
__device__ __forceinline__ uint64_t make_desc(uint32_t addr, uint32_t lbo_bytes) {
    return (uint64_t)((addr & 0x3FFFF) >> 4) | ((uint64_t)(lbo_bytes >> 4) << 16) | ((uint64_t)64 << 32) | ((uint64_t)1 << 62);
}

__device__ __forceinline__ void wgmma_n96_ss_ta(float (&d)[48], uint64_t da, uint64_t db, int scale_d) {
    asm volatile("{\n.reg .pred p;\nsetp.ne.b32 p, %50, 0;\n"
        "wgmma.mma_async.sync.aligned.m64n96k16.f32.bf16.bf16 "
        "{%0, %1, %2, %3, %4, %5, %6, %7, %8, %9, %10, %11, %12, %13, %14, %15, "
        "%16, %17, %18, %19, %20, %21, %22, %23, %24, %25, %26, %27, %28, %29, %30, %31, "
        "%32, %33, %34, %35, %36, %37, %38, %39, %40, %41, %42, %43, %44, %45, %46, %47}, "
        "%48, %49, p, 1, 1, 1, 0;\n}\n"
        : "+f"(d[0]), "+f"(d[1]), "+f"(d[2]), "+f"(d[3]), "+f"(d[4]), "+f"(d[5]), "+f"(d[6]), "+f"(d[7]),
          "+f"(d[8]), "+f"(d[9]), "+f"(d[10]), "+f"(d[11]), "+f"(d[12]), "+f"(d[13]), "+f"(d[14]), "+f"(d[15]),
          "+f"(d[16]), "+f"(d[17]), "+f"(d[18]), "+f"(d[19]), "+f"(d[20]), "+f"(d[21]), "+f"(d[22]), "+f"(d[23]),
          "+f"(d[24]), "+f"(d[25]), "+f"(d[26]), "+f"(d[27]), "+f"(d[28]), "+f"(d[29]), "+f"(d[30]), "+f"(d[31]),
          "+f"(d[32]), "+f"(d[33]), "+f"(d[34]), "+f"(d[35]), "+f"(d[36]), "+f"(d[37]), "+f"(d[38]), "+f"(d[39]),
          "+f"(d[40]), "+f"(d[41]), "+f"(d[42]), "+f"(d[43]), "+f"(d[44]), "+f"(d[45]), "+f"(d[46]), "+f"(d[47])
        : "l"(da), "l"(db), "r"(scale_d));
}
__device__ __forceinline__ void wgmma_n128_ss(float (&d)[64], uint64_t da, uint64_t db, int scale_d) {
    asm volatile("{\n.reg .pred p;\nsetp.ne.b32 p, %66, 0;\n"
        "wgmma.mma_async.sync.aligned.m64n128k16.f32.bf16.bf16 "
        "{%0, %1, %2, %3, %4, %5, %6, %7, %8, %9, %10, %11, %12, %13, %14, %15, "
        "%16, %17, %18, %19, %20, %21, %22, %23, %24, %25, %26, %27, %28, %29, %30, %31, "
        "%32, %33, %34, %35, %36, %37, %38, %39, %40, %41, %42, %43, %44, %45, %46, %47, "
        "%48, %49, %50, %51, %52, %53, %54, %55, %56, %57, %58, %59, %60, %61, %62, %63}, "
        "%64, %65, p, 1, 1, 0, 0;\n}\n"
        : "+f"(d[0]), "+f"(d[1]), "+f"(d[2]), "+f"(d[3]), "+f"(d[4]), "+f"(d[5]), "+f"(d[6]), "+f"(d[7]),
          "+f"(d[8]), "+f"(d[9]), "+f"(d[10]), "+f"(d[11]), "+f"(d[12]), "+f"(d[13]), "+f"(d[14]), "+f"(d[15]),
          "+f"(d[16]), "+f"(d[17]), "+f"(d[18]), "+f"(d[19]), "+f"(d[20]), "+f"(d[21]), "+f"(d[22]), "+f"(d[23]),
          "+f"(d[24]), "+f"(d[25]), "+f"(d[26]), "+f"(d[27]), "+f"(d[28]), "+f"(d[29]), "+f"(d[30]), "+f"(d[31]),
          "+f"(d[32]), "+f"(d[33]), "+f"(d[34]), "+f"(d[35]), "+f"(d[36]), "+f"(d[37]), "+f"(d[38]), "+f"(d[39]),
          "+f"(d[40]), "+f"(d[41]), "+f"(d[42]), "+f"(d[43]), "+f"(d[44]), "+f"(d[45]), "+f"(d[46]), "+f"(d[47]),
          "+f"(d[48]), "+f"(d[49]), "+f"(d[50]), "+f"(d[51]), "+f"(d[52]), "+f"(d[53]), "+f"(d[54]), "+f"(d[55]),
          "+f"(d[56]), "+f"(d[57]), "+f"(d[58]), "+f"(d[59]), "+f"(d[60]), "+f"(d[61]), "+f"(d[62]), "+f"(d[63])
        : "l"(da), "l"(db), "r"(scale_d));
}
__device__ __forceinline__ void wgmma_n128_rs_tb(float (&d)[64], uint32_t a0, uint32_t a1, uint32_t a2, uint32_t a3, uint64_t db, int scale_d) {
    asm volatile("{\n.reg .pred p;\nsetp.ne.b32 p, %69, 0;\n"
        "wgmma.mma_async.sync.aligned.m64n128k16.f32.bf16.bf16 "
        "{%0, %1, %2, %3, %4, %5, %6, %7, %8, %9, %10, %11, %12, %13, %14, %15, "
        "%16, %17, %18, %19, %20, %21, %22, %23, %24, %25, %26, %27, %28, %29, %30, %31, "
        "%32, %33, %34, %35, %36, %37, %38, %39, %40, %41, %42, %43, %44, %45, %46, %47, "
        "%48, %49, %50, %51, %52, %53, %54, %55, %56, %57, %58, %59, %60, %61, %62, %63}, "
        "{%64, %65, %66, %67}, %68, p, 1, 1, 1;\n}\n"
        : "+f"(d[0]), "+f"(d[1]), "+f"(d[2]), "+f"(d[3]), "+f"(d[4]), "+f"(d[5]), "+f"(d[6]), "+f"(d[7]),
          "+f"(d[8]), "+f"(d[9]), "+f"(d[10]), "+f"(d[11]), "+f"(d[12]), "+f"(d[13]), "+f"(d[14]), "+f"(d[15]),
          "+f"(d[16]), "+f"(d[17]), "+f"(d[18]), "+f"(d[19]), "+f"(d[20]), "+f"(d[21]), "+f"(d[22]), "+f"(d[23]),
          "+f"(d[24]), "+f"(d[25]), "+f"(d[26]), "+f"(d[27]), "+f"(d[28]), "+f"(d[29]), "+f"(d[30]), "+f"(d[31]),
          "+f"(d[32]), "+f"(d[33]), "+f"(d[34]), "+f"(d[35]), "+f"(d[36]), "+f"(d[37]), "+f"(d[38]), "+f"(d[39]),
          "+f"(d[40]), "+f"(d[41]), "+f"(d[42]), "+f"(d[43]), "+f"(d[44]), "+f"(d[45]), "+f"(d[46]), "+f"(d[47]),
          "+f"(d[48]), "+f"(d[49]), "+f"(d[50]), "+f"(d[51]), "+f"(d[52]), "+f"(d[53]), "+f"(d[54]), "+f"(d[55]),
          "+f"(d[56]), "+f"(d[57]), "+f"(d[58]), "+f"(d[59]), "+f"(d[60]), "+f"(d[61]), "+f"(d[62]), "+f"(d[63])
        : "r"(a0), "r"(a1), "r"(a2), "r"(a3), "l"(db), "r"(scale_d));
}

template <bool SCALE>
__device__ __forceinline__ void store_tile_t(float (&acc)[48], uint32_t base, int wq, int lane) {
    if (SCALE) {
#pragma unroll
        for (int i = 0; i < 48; i++) acc[i] *= QSCALE;
    }
    const int mat = lane >> 3, r = lane & 7;
    const uint32_t a = base + (uint32_t)((mat >> 1) * 8 + r) * 128 + (uint32_t)((2 * wq + (mat & 1)) ^ r) * 16;
#pragma unroll
    for (int s = 0; s < 6; s++)
        stsm_x4_t(a + s * 16 * 128, pack_bf16(acc[8 * s + 0], acc[8 * s + 1]), pack_bf16(acc[8 * s + 2], acc[8 * s + 3]),
                  pack_bf16(acc[8 * s + 4], acc[8 * s + 5]), pack_bf16(acc[8 * s + 6], acc[8 * s + 7]));
}

__device__ __forceinline__ constexpr bool step_peer(int i) { return (0x170 >> i) & 1; }
__device__ __forceinline__ int step_col(int i, int rank, int kp) {
    const int idx = i == 0 ? 0 : 1 + 4 * rank + (i < 7 ? (i - 1) % 3 : 3);
    return (idx + kp) % NOT;
}
__device__ __forceinline__ constexpr uint32_t stage_off(int e) { return e == 1 ? STAGE2_OFF : e == 3 ? QO_BYTES + 2 * SLOT_BYTES : X4_OFF; }
__device__ __forceinline__ uint32_t map_peer(uint32_t addr, int rank) {
    uint32_t r;
    asm volatile("mapa.shared::cluster.u32 %0, %1, %2;" : "=r"(r) : "r"(addr), "r"(rank ^ 1));
    return r;
}
__device__ __forceinline__ void mbar_arrive_remote(uint32_t bar) {
    asm volatile("mbarrier.arrive.shared::cluster.b64 _, [%0];" ::"r"(bar) : "memory");
}

__device__ __forceinline__ constexpr uint32_t x_off(int j) { return (j == 4 || j == NQC - 1) ? X4_OFF : (j % NSLOT) * XCH_BYTES; }

template <bool TWO>
__device__ __forceinline__ void qproj(uint32_t sbase, uint32_t qrdy, int wg, int wq, int lane) {
    const uint32_t slot0 = sbase + QO_BYTES;
    const uint32_t full0 = sbase + BAR_OFF, empty0 = full0 + 8 * NSLOT;
    float acc0[48], acc1[48];
#pragma unroll
    for (int j = 0; j < NQC; j++) {
        const int s = j % NSLOT;
        mbar_wait(full0 + 8 * s, (j / NSLOT) & 1);
        const uint64_t da = make_desc(slot0 + s * SLOT_BYTES + wg * 8192, 16);
        const uint64_t db = make_desc(sbase + x_off(j), 16);
        wg_fence();
        wgmma_n96_ss_ta(acc0, da, db, j != 0);
        if (TWO) wgmma_n96_ss_ta(acc1, da + 512, db, j != 0);
        wg_commit();
        if (j > 0) {
            wg_wait<1>();
            if (lane == 0) mbar_arrive(empty0 + 8 * ((j - 1) % NSLOT), 1);
        }
#pragma unroll
        for (int k = 1; k < 4; k++) {
            wgmma_n96_ss_ta(acc0, da + k * 128, db + k * 2, 1);
            if (TWO) wgmma_n96_ss_ta(acc1, da + 512 + k * 128, db + k * 2, 1);
        }
        wg_commit();
        bar_consumers();
    }
    wg_wait<0>();
    reg_fence(acc0);
    if (TWO) reg_fence(acc1);
    if (lane == 0) mbar_arrive(empty0 + 8 * ((NQC - 1) % NSLOT), 1);
    store_tile_t<true>(acc0, sbase + (wg & 1) * QHALF + (wg >> 1) * (SQ * 128), wq, lane);
    if (TWO) store_tile_t<true>(acc1, sbase + QHALF + SQ * 128, wq, lane);
    fence_async_smem();
    __syncwarp();
    if (lane == 0) mbar_arrive(qrdy, 1);
}

struct RowState { float m0, m1, l0, l1; bool zero_ref; int slot; uint32_t phase; };

template <bool LAST>
__device__ __forceinline__ void attn_tile(float (&o)[64], RowState& st, uint32_t sbase, uint64_t dq, int wg, int lane, int t,
                                          uint32_t credit, int rank) {
    const uint32_t slot0 = sbase + QO_BYTES, full0 = sbase + BAR_OFF, empty0 = full0 + 8 * NSLOT;
    float &m0 = st.m0, &m1 = st.m1, &l0 = st.l0, &l1 = st.l1;
    bool& zero_ref = st.zero_ref;
    int& slot = st.slot;
    uint32_t& phase = st.phase;
    constexpr int PA = LAST ? 8 : PVA;
    float s[64];
    {
        mbar_wait(full0 + 8 * slot, phase);
        const uint64_t dk = make_desc(slot0 + slot * SLOT_BYTES, 16);
        token_wait(wg);
        wg_fence();
#pragma unroll
        for (int k = 0; k < 8; k++) {
            wgmma_n128_ss(s, dq + (k >> 2) * (QHALF >> 4) + (k & 3) * 2, dk + (k >> 2) * 1024 + (k & 3) * 2, k != 0);
            if (k == SPLIT - 1) wg_commit();
        }
        wg_commit();
        wg_wait<1>();
        token_pass(wg);
        wg_wait<0>();
        reg_fence(s);
        if (lane == 0) mbar_arrive(empty0 + 8 * slot, 1);
        if (!LAST && t == NKT - 2 && lane == 0) mbar_arrive_remote(map_peer(credit, rank));
        if (++slot == NSLOT) { slot = 0; phase ^= 1; }
    }
    {
        int ia0 = max(__float_as_int(s[0]), __float_as_int(s[1])), ia1 = max(__float_as_int(s[2]), __float_as_int(s[3]));
        int ib0 = max(__float_as_int(s[4]), __float_as_int(s[5])), ib1 = max(__float_as_int(s[6]), __float_as_int(s[7]));
#pragma unroll
        for (int j = 1; j < 8; j++) {
            ia0 = __vimax3_s32(ia0, __float_as_int(s[8 * j + 0]), __float_as_int(s[8 * j + 1]));
            ia1 = __vimax3_s32(ia1, __float_as_int(s[8 * j + 2]), __float_as_int(s[8 * j + 3]));
            ib0 = __vimax3_s32(ib0, __float_as_int(s[8 * j + 4]), __float_as_int(s[8 * j + 5]));
            ib1 = __vimax3_s32(ib1, __float_as_int(s[8 * j + 6]), __float_as_int(s[8 * j + 7]));
        }
        const float th0 = m0 + 16.f, th1 = m1 + 16.f;
        const int ti0 = th0 >= 0.f ? __float_as_int(th0) : INT_MIN, ti1 = th1 >= 0.f ? __float_as_int(th1) : INT_MIN;
        if (__any_sync(0xffffffffu, max(ia0, ib0) >= ti0 || max(ia1, ib1) >= ti1)) {
            float mx0 = m0, mx1 = m1;
#pragma unroll
            for (int j = 0; j < 16; j++) {
                mx0 = fmaxf(mx0, fmaxf(s[4 * j], s[4 * j + 1]));
                mx1 = fmaxf(mx1, fmaxf(s[4 * j + 2], s[4 * j + 3]));
            }
            mx0 = fmaxf(mx0, __shfl_xor_sync(0xffffffffu, mx0, 1));
            mx1 = fmaxf(mx1, __shfl_xor_sync(0xffffffffu, mx1, 1));
            mx0 = fmaxf(mx0, __shfl_xor_sync(0xffffffffu, mx0, 2));
            mx1 = fmaxf(mx1, __shfl_xor_sync(0xffffffffu, mx1, 2));
            zero_ref = !LAST && t == 0 && __all_sync(0xffffffffu, mx0 >= -40.f && mx0 < 16.f && mx1 >= -40.f && mx1 < 16.f);
            if (zero_ref) { mx0 = 0.f; mx1 = 0.f; }
            const float a0 = ex2(m0 - mx0), a1 = ex2(m1 - mx1);
            m0 = mx0; m1 = mx1;
            l0 *= a0; l1 *= a1;
#pragma unroll
            for (int j = 0; j < 16; j++) { o[4 * j] *= a0; o[4 * j + 1] *= a0; o[4 * j + 2] *= a1; o[4 * j + 3] *= a1; }
        }
        if (!zero_ref) {
#pragma unroll
            for (int j = 0; j < 16; j++) { s[4 * j] -= m0; s[4 * j + 1] -= m0; s[4 * j + 2] -= m1; s[4 * j + 3] -= m1; }
        }
    }
    uint32_t p[32];
    auto exp_block = [&](int j) {
        const float e0 = ex2(s[4 * j + 0]), e1 = ex2(s[4 * j + 1]), e2 = ex2(s[4 * j + 2]), e3 = ex2(s[4 * j + 3]);
        l0 += e0 + e1; l1 += e2 + e3;
        p[2 * j] = pack_bf16(e0, e1);
        p[2 * j + 1] = pack_bf16(e2, e3);
    };
#pragma unroll
    for (int j = 0; j < 2 * PA; j++) exp_block(j);
    mbar_wait(full0 + 8 * slot, phase);
    const uint64_t dv = make_desc(slot0 + slot * SLOT_BYTES, 16384);
    token_wait(wg);
    wg_fence();
#pragma unroll
    for (int k = 0; k < PA; k++) {
        wgmma_n128_rs_tb(o, p[4 * k], p[4 * k + 1], p[4 * k + 2], p[4 * k + 3], dv + k * 128, 1);
        if (LAST && k == SPLIT - 1) wg_commit();
    }
    wg_commit();
    if (!LAST) {
        mbar_wait(full0 + 8 * slot, phase);
#pragma unroll
        for (int j = 2 * PA; j < 16; j++) exp_block(j);
        wg_fence();
#pragma unroll
        for (int k = PA; k < 8; k++) wgmma_n128_rs_tb(o, p[4 * k], p[4 * k + 1], p[4 * k + 2], p[4 * k + 3], dv + k * 128, 1);
        wg_commit();
    } else {
        wg_wait<1>();
    }
    token_pass(wg);
    if (LAST) {
        l0 += __shfl_xor_sync(0xffffffffu, l0, 1); l1 += __shfl_xor_sync(0xffffffffu, l1, 1);
        l0 += __shfl_xor_sync(0xffffffffu, l0, 2); l1 += __shfl_xor_sync(0xffffffffu, l1, 2);
        asm volatile("rcp.approx.ftz.f32 %0, %0;" : "+f"(l0));
        asm volatile("rcp.approx.ftz.f32 %0, %0;" : "+f"(l1));
    }
    wg_wait<0>();
    reg_fence(o);
    if (lane == 0) mbar_arrive(empty0 + 8 * slot, 1);
    if (++slot == NSLOT) { slot = 0; phase ^= 1; }
}

__global__ void __cluster_dims__(2, 1, 1) __launch_bounds__(NTHREADS, 1)
gqa_fused_kernel(const __grid_constant__ CUtensorMap tm_x, const __grid_constant__ CUtensorMap tm_wq,
                 const __grid_constant__ CUtensorMap tm_k, const __grid_constant__ CUtensorMap tm_v,
                 const __grid_constant__ CUtensorMap tm_wo, const __grid_constant__ CUtensorMap tm_out,
                 __nv_bfloat16* __restrict__ out, const uint8_t* __restrict__ x_raw, const uint8_t* __restrict__ wq_raw,
                 const uint8_t* __restrict__ k_raw, const uint8_t* __restrict__ v_raw, int clear_out, int map_mode) {
    extern __shared__ __align__(1024) uint8_t smem_raw[];
    const uint32_t sbase = (smem_u32(smem_raw) + 1023u) & ~1023u;
    const uint32_t slot0 = sbase + QO_BYTES;
    const uint32_t full0 = sbase + BAR_OFF, empty0 = full0 + 8 * NSLOT;
    const uint32_t qrdy0 = full0 + 80, ordy0 = full0 + 96, zgo = full0 + 112, ost0 = full0 + 120, credit = full0 + 144;
    const uint32_t orecv = full0 + 152, gotit = full0 + 160, sfull0 = full0 + 168, sfree0 = full0 + 208;
    const uint32_t orecv1 = full0 + 232, orecv2 = full0 + 248;
    const int tid = threadIdx.x, lane = tid & 31;
    const int warp = __shfl_sync(0xffffffffu, tid >> 5, 0), wg = warp >> 2, wq = warp & 3;

    if (blockIdx.x >= NCTA) {
        wait_until_ns(global_ns() + XTRA_T0);
        for (int i = tid; i < XTRA * 32 * 64; i += NTHREADS) {
            const int piece = TOUCH_N + (i >> 11), item = (blockIdx.x - NCTA) * 32 + ((i >> 6) & 31), line = i & 63;
            prefetch_l2(((piece & 4) ? v_raw : k_raw) + (size_t)item * (SK * DH * 2) + (piece >> 3) * SLOT_BYTES + (piece & 3) * 8192 + line * 128);
        }
        return;
    }
    const int cl = blockIdx.x >> 1, rank = blockIdx.x & 1;
    int kp = cl & 7, b = cl >> 3;
    if (map_mode) {
        kp = cl < 4 ? 1 : cl < 36 ? (cl - 4) & 7 : ((cl - 36) % 7 == 0 ? 0 : (cl - 36) % 7 + 1);
        b = cl < 4 ? 4 + cl : cl < 36 ? (cl - 4) >> 3 : 4 + (cl - 36) / 7;
    }
    const int kvh = kp * 2 + rank;

    if (tid == 384) {
        prefetch_tm(&tm_wq); prefetch_tm(&tm_x);
#pragma unroll
        for (int i = 0; i < NSLOT; i++) mbar_init(full0 + 8 * i, 1);
        asm volatile("fence.mbarrier_init.release.cluster;" ::: "memory");
#pragma unroll
        for (int j = 0; j < NSLOT; j++) {
            const uint32_t bar = full0 + 8 * j;
            mbar_expect_tx(bar, SLOT_BYTES + XCH_BYTES);
            tma_3d(slot0 + j * SLOT_BYTES, &tm_wq, 0, j * 64, kvh * 4, bar);
            tma_2d(sbase + x_off(j), &tm_x, j * 64, b * SQ, bar);
        }
    }
    if (tid == 448) {
#pragma unroll
        for (int i = 0; i < NSLOT; i++) mbar_init(empty0 + 8 * i, 12);
        mbar_init(qrdy0, 8); mbar_init(qrdy0 + 8, 4); mbar_init(ordy0, 6); mbar_init(ordy0 + 8, 6); mbar_init(zgo, 1);
#pragma unroll
        for (int i = 0; i < 3; i++) mbar_init(ost0 + 8 * i, 4);
        mbar_init(sfree0, 1); mbar_init(sfree0 + 8, 1);
#pragma unroll
        for (int i = 0; i < 5; i++) mbar_init(sfull0 + 8 * i, 4);
        mbar_init(credit, 12); mbar_init(orecv, 1); mbar_init(orecv1, 1); mbar_init(orecv2, 1); mbar_init(gotit, 1);
        asm volatile("fence.mbarrier_init.release.cluster;" ::: "memory");
        mbar_expect_tx(orecv, 32768); mbar_expect_tx(orecv1, 8192); mbar_expect_tx(orecv2, 8192);
    }
    if (tid == 480) asm volatile("st.shared.b64 [%0], %1;" ::"r"(sbase + TSTART_OFF), "l"(global_ns()) : "memory");
    __syncthreads();
    asm volatile("barrier.cluster.arrive.relaxed.aligned;" ::: "memory");

    if (wg == 3) {
        asm volatile("setmaxnreg.dec.sync.aligned.u32 32;");
        if (warp == 12) {
            const int kvrow = (b * HKV + kvh) * SK;
            long long tstart;
            asm volatile("ld.shared.b64 %0, [%1];" : "=l"(tstart) : "r"(sbase + TSTART_OFF) : "memory");
            int s = 0, ph = 0;
            for (int g = NSLOT; g < NQC + 2 * NKT; g++) {
                const uint32_t bar = full0 + 8 * s;
                const int i = g - NQC;
                mbar_wait(empty0 + 8 * s, ph);
                if (i >= 3) {
                    mbar_wait(full0 + 8 * ((g - CAP) % NSLOT), ((g - CAP) / NSLOT) & 1);
                    const long long due = tstart + PACE_A + PACE_T * (i - 4) + ((b & 1) ? SKEW : -SKEW) * (i - 3) / 12 +
                                          (i == 2 * NKT - 1 ? VLATE : i == 2 * NKT - 3 ? VLATE / 2 : 0);
                    wait_until_ns(due);
                }
                if (lane == 0) {
                    if (i < 0) {
                        mbar_expect_tx(bar, SLOT_BYTES + XCH_BYTES);
                        tma_3d(slot0 + s * SLOT_BYTES, &tm_wq, 0, g * 64, kvh * 4, bar);
                        if (g < NQC - 1) tma_2d(sbase + x_off(g), &tm_x, g * 64, b * SQ, bar);
                    } else {
                        if (i == 0) tma_2d(sbase + X4_OFF, &tm_x, (NQC - 1) * 64, b * SQ, full0 + 8 * ((NQC - 1) % NSLOT));
                        mbar_expect_tx(bar, SLOT_BYTES);
                        tma_3d(slot0 + s * SLOT_BYTES, (i & 1) ? &tm_v : &tm_k, 0, kvrow + (i >> 1) * 128, 0, bar);
                        if (i == ZERO_I) mbar_arrive(zgo, 1);
                    }
                }
                if (++s == NSLOT) { s = 0; ph ^= 1; }
            }
            mbar_wait(full0 + 8 * 4, 0);
#pragma unroll
            for (int i = 0; i < NOT; i++) {
                if (i == 3 || i == 4) continue;
                const int sl = 2 + i % 3, col = step_col(i, rank, kp);
                if (i == 6 || i == 7) mbar_wait(full0 + 8 * sl, 0);
                mbar_wait(empty0 + 8 * sl, (i / 3) & 1);
                if (lane == 0) {
                    mbar_expect_tx(full0 + 8 * sl, SLOT_BYTES);
                    tma_2d(slot0 + sl * SLOT_BYTES, &tm_wo, col * 64, (step_peer(i) ? kvh ^ 1 : kvh) * 256, full0 + 8 * sl);
                }
            }
        } else if (warp == 13) {
            mbar_wait(full0, 0);
            if (lane == 0) { prefetch_tm(&tm_k); prefetch_tm(&tm_v); prefetch_tm(&tm_wo); prefetch_tm(&tm_out); }
#pragma unroll
            for (int i = lane; i < (NQC - NSLOT) * 32; i += 32)
                prefetch_l2(wq_raw + (size_t)(NSLOT * 64 + (i >> 2) * 8 + b) * (HQ * DH * 2) + kvh * 512 + (i & 3) * 128);
            if (lane < (NQC - NSLOT) * 6) prefetch_l2(x_raw + (size_t)(b * SQ + kvh * 6 + lane % 6) * (DM * 2) + (NSLOT + lane / 6) * 128);
            const size_t kvoff = (size_t)(b * HKV + kvh) * SK * DH * 2;
            const long long t0 = clock64();
            for (int i = 0; i < TOUCH_N; i++) {
                while (clock64() - t0 < TOUCH_D0 + i * TOUCH_DT) {}
                const uint8_t* pp = ((i & 4) ? v_raw : k_raw) + kvoff + (size_t)(i >> 3) * SLOT_BYTES + (i & 3) * 8192 + lane * 32;
#pragma unroll
                for (int o = 0; o < 8; o++)
                    asm volatile("cp.async.ca.shared.global [%0], [%1], 4;" ::"r"(sbase + DUMMY_OFF + lane * 4), "l"(pp + o * 1024) : "memory");
            }
            asm volatile("cp.async.wait_all;" ::: "memory");
        } else if (warp == 14) {
            asm volatile("barrier.cluster.wait.aligned;" ::: "memory");
            if (clear_out) {
                mbar_wait(zgo, 0);
                uint4* z = reinterpret_cast<uint4*>(out + (size_t)(b * SQ + kvh * 6) * DM);
                for (int i = lane; i < 6 * DM * 2 / 16; i += 32) z[i] = make_uint4(0, 0, 0, 0);
                asm volatile("fence.proxy.async.global;" ::: "memory");
                __syncwarp();
                if (lane == 0) {
                    __threadfence();
                    const unsigned target = (atomicAdd(&g_cnt[b * 32], 1u) / HKV + 1) * HKV;
                    for (int it = 0; it < (1 << 16); it++) {
                        unsigned v;
                        asm volatile("ld.acquire.gpu.global.u32 %0, [%1];" : "=r"(v) : "l"(&g_cnt[b * 32]) : "memory");
                        if ((int)(v - target) >= 0) break;
                        __nanosleep(200);
                    }
                    asm volatile("fence.proxy.async.global;" ::: "memory");
                }
            }
            if (lane == 0) {
                const uint32_t peer = map_peer(sbase, rank);
                mbar_wait(credit, 0);
#pragma unroll
                for (int n = 0; n < 6; n++) {
                    const int w = n >> 1, h = n & 1;
                    if (h == 0) mbar_wait(ost0 + 8 * w, 0);
                    if (w == 2) {
                        mbar_wait(empty0 + 8 * (2 + h), 1);
                        mbar_expect_tx(full0 + 8 * (2 + h), SLOT_BYTES);
                        tma_2d(slot0 + (2 + h) * SLOT_BYTES, &tm_wo, step_col(3 + h, rank, kp) * 64, (h ? kvh ^ 1 : kvh) * 256, full0 + 8 * (2 + h));
                    }
                    asm volatile("cp.async.bulk.shared::cluster.shared::cta.mbarrier::complete_tx::bytes [%0], [%1], %2, [%3];"
                                 ::"r"(peer + PEER_OFF + h * QHALF + w * 8192), "r"(sbase + h * QHALF + w * 8192), "r"(8192),
                                   "r"(peer + ((w < 2 ? orecv : h ? orecv2 : orecv1) - sbase)) : "memory");
                }
#pragma unroll
                for (int e = 0; e < 5; e++) {
                    const int col = step_col(e == 0 ? 0 : e == 4 ? 8 : 3 + e, rank, kp);
                    mbar_wait(sfull0 + 8 * e, 0);
                    if (e < 2) {
                        if (e == 0) mbar_wait(empty0 + 8 * 4, 1);
                        mbar_wait(empty0 + 8 * (e == 0 ? 2 : 4), 0);
                        const long long tg = clock64();
                        while (clock64() - tg < GATE) {}
                    }
                    asm volatile("cp.reduce.async.bulk.tensor.2d.global.shared::cta.add.tile.bulk_group [%0, {%2, %3}], [%1];"
                                 ::"l"(&tm_out), "r"(sbase + stage_off(e)), "r"(col * 64), "r"(b * SQ) : "memory");
                    asm volatile("cp.async.bulk.commit_group;" ::: "memory");
                    if (e == 1) mbar_arrive_remote(peer + (gotit - sbase));
                    if (e == 0 || e == 3) {
                        if (e == 0) asm volatile("cp.async.bulk.wait_group.read 0;" ::: "memory");
                        else asm volatile("cp.async.bulk.wait_group.read 1;" ::: "memory");
                        mbar_arrive(sfree0 + (e ? 8 : 0), 1);
                    }
                }
                mbar_wait(gotit, 0);
                asm volatile("cp.async.bulk.wait_group.read 0;" ::: "memory");
            }
        }
    } else {
        asm volatile("setmaxnreg.inc.sync.aligned.u32 160;");
        if (wg == 2) qproj<true>(sbase, qrdy0 + 8, wg, wq, lane);
        else qproj<false>(sbase, qrdy0, wg, wq, lane);
        asm volatile("barrier.cluster.wait.aligned;" ::: "memory");
        if (wg == 2) token_pass(2);
        if (wg < 2) mbar_wait(qrdy0, 0);
        if (wg > 0) mbar_wait(qrdy0 + 8, 0);
        float o[64];
#pragma unroll
        for (int j = 0; j < 64; j++) o[j] = 0.f;
        RowState rs = {-INFINITY, -INFINITY, 0.f, 0.f, false, NQC % NSLOT, (NQC / NSLOT) & 1};
        const uint64_t dq = make_desc(sbase + wg * 8192, 16);
#pragma unroll 1
        for (int t = 0; t < NKT - 1; t++) {
            attn_tile<false>(o, rs, sbase, dq, wg, lane, t, credit, rank);
        }
        attn_tile<true>(o, rs, sbase, dq, wg, lane, NKT - 1, credit, rank);
        const float l0 = rs.l0, l1 = rs.l1;
        {
            const int mat = lane >> 3, r = lane & 7;
            const uint32_t rowaddr = sbase + (uint32_t)(wg * 64 + wq * 16 + (mat & 1) * 8 + r) * 128;
#pragma unroll
            for (int j = 0; j < 8; j++) {
                const uint32_t chunk = (uint32_t)(((2 * j + (mat >> 1)) & 7) ^ r);
                stsm_x4(rowaddr + (j >> 2) * QHALF + chunk * 16,
                        pack_bf16(o[8 * j + 0] * l0, o[8 * j + 1] * l0), pack_bf16(o[8 * j + 2] * l1, o[8 * j + 3] * l1),
                        pack_bf16(o[8 * j + 4] * l0, o[8 * j + 5] * l0), pack_bf16(o[8 * j + 6] * l1, o[8 * j + 7] * l1));
            }
            fence_async_smem();
            __syncwarp();
            if (lane == 0) {
                mbar_arrive(ordy0 + (warp < 6 ? 0 : 8), 1);
                mbar_arrive(ost0 + 8 * wg, 1);
            }
        }
        float acc[48];
        auto mma_half = [&](uint64_t da, uint64_t db, int h, bool fresh, bool commit) {
#pragma unroll
            for (int k = 0; k < 8; k++) {
                wgmma_n96_ss_ta(acc, da + (8 * h + k) * 128, db + (h * (SQ * 128) + (k >> 2) * QHALF + (k & 3) * 32) / 16, k != 0 || !fresh);
                if (commit && k == SPLIT_O - 1) wg_commit();
            }
        };
#pragma unroll
        for (int st = 0; st < 3; st++) {
            if (st == 2 && wg == 2) break;
            const int i = 3 * st + wg, s = 2 + wg;
            const bool peer = step_peer(i);
            mbar_wait(full0 + 8 * s, (1 + st) & 1);
            const uint64_t da = make_desc(slot0 + s * SLOT_BYTES, 16);
            const uint64_t db = make_desc(sbase + (peer ? PEER_OFF : 0), 16);
            if (st == 0) mbar_wait(ordy0, 0);
            if (st > 0 && peer) mbar_wait(st == 1 ? orecv : orecv2, 0);
            token_wait(wg);
            wg_fence();
            mma_half(da, db, 0, !peer, false);
            if (st == 0) {
                mbar_wait(ordy0 + 8, 0);
                wg_fence();
                mma_half(da, db, 1, false, true);
            } else if (st == 1) {
#pragma unroll
                for (int k = 0; k < 8; k++) {
                    if ((k & 3) == 0) {
                        if (peer) mbar_wait(k ? orecv2 : orecv1, 0);
                        wg_fence();
                    }
                    wgmma_n96_ss_ta(acc, da + (8 + k) * 128, db + (SQ * 128 + (k >> 2) * QHALF + (k & 3) * 32) / 16, 1);
                    if (k == SPLIT_O - 1) wg_commit();
                }
            } else {
                mma_half(da, db, 1, false, true);
                if (wg == 1) {
                    mbar_wait(full0 + 8 * 4, 1);
                    wg_fence();
                    const uint64_t da2 = make_desc(slot0 + 4 * SLOT_BYTES, 16), db2 = make_desc(sbase + PEER_OFF, 16);
                    mma_half(da2, db2, 0, false, false);
                    mma_half(da2, db2, 1, false, false);
                }
            }
            wg_commit();
            if (i < 7) {
                wg_wait<1>();
                token_pass(wg);
            }
            const bool done = st == 2 || peer || i == 0;
            const int e = i == 0 ? 0 : i - 3;
            if (e == 2 || e == 4) mbar_wait(sfree0 + 4 * (e - 2), 0);
            wg_wait<0>();
            reg_fence(acc);
            if (st < 2 && lane == 0) mbar_arrive(empty0 + 8 * s, 3);
            if (done) {
                if (st == 2 && wg == 0) asm volatile("bar.sync 5, 128;" ::: "memory");
                store_tile_t<false>(acc, sbase + stage_off(e), wq, lane);
                fence_async_smem();
                __syncwarp();
                if (lane == 0) mbar_arrive(sfull0 + 8 * e, 1);
            }
        }
    }
}

typedef CUresult (*EncodeFn)(CUtensorMap*, CUtensorMapDataType, cuuint32_t, void*, const cuuint64_t*, const cuuint64_t*,
                             const cuuint32_t*, const cuuint32_t*, CUtensorMapInterleave, CUtensorMapSwizzle,
                             CUtensorMapL2promotion, CUtensorMapFloatOOBfill);

void encode(EncodeFn fn, CUtensorMap* tm, const void* ptr, int rank, const cuuint64_t* dims, const cuuint64_t* strides,
            const cuuint32_t* box, CUtensorMapL2promotion prom) {
    const cuuint32_t es[3] = {1, 1, 1};
    fn(tm, CU_TENSOR_MAP_DATA_TYPE_BFLOAT16, rank, const_cast<void*>(ptr), dims, strides, box, es,
       CU_TENSOR_MAP_INTERLEAVE_NONE, CU_TENSOR_MAP_SWIZZLE_128B, prom,
       CU_TENSOR_MAP_FLOAT_OOB_FILL_NONE);
}

__global__ void occupancy_probe_kernel() {}

int max_clusters(int size) {
    cudaLaunchConfig_t cfg = {};
    cfg.gridDim = dim3(NCTA);
    cfg.blockDim = dim3(NTHREADS);
    cfg.dynamicSmemBytes = SMEM_BYTES;
    cudaLaunchAttribute at;
    at.id = cudaLaunchAttributeClusterDimension;
    at.val.clusterDim.x = size; at.val.clusterDim.y = 1; at.val.clusterDim.z = 1;
    cfg.attrs = &at;
    cfg.numAttrs = 1;
    int n = 0;
    if (cudaOccupancyMaxActiveClusters(&n, occupancy_probe_kernel, &cfg) != cudaSuccess) n = 0;
    (void)cudaGetLastError();
    return n;
}

}

extern "C" void kernel_launch(void* const* d_in, const int* in_sizes, int n_in, void* d_out, int out_size) {
    (void)in_sizes; (void)n_in; (void)out_size;
    static EncodeFn fn = nullptr;
    static int pairs = 0, map_mode = 0;
    if (!fn) {
        void* p = nullptr;
        cudaDriverEntryPointQueryResult qr;
        cudaGetDriverEntryPoint("cuTensorMapEncodeTiled", &p, cudaEnableDefault, &qr);
        fn = (EncodeFn)p;
        cudaFuncSetAttribute(gqa_fused_kernel, cudaFuncAttributeMaxDynamicSharedMemorySize, SMEM_BYTES);
        cudaFuncSetAttribute(occupancy_probe_kernel, cudaFuncAttributeMaxDynamicSharedMemorySize, SMEM_BYTES);
        cudaFuncSetAttribute(occupancy_probe_kernel, cudaFuncAttributeNonPortableClusterSizeAllowed, 1);
        pairs = max_clusters(2);
        map_mode = pairs == 66 && max_clusters(4) == 30 && max_clusters(8) == 15 && max_clusters(16) == 7;
    }
    CUtensorMap tx, twq, tk, tv, two, tout;
    {
        const cuuint64_t d[2] = {DM, NB * SQ}, s[1] = {DM * 2};
        const cuuint32_t bx[2] = {64, SQ};
        encode(fn, &tx, d_in[0], 2, d, s, bx, CU_TENSOR_MAP_L2_PROMOTION_L2_128B);
        encode(fn, &tout, d_out, 2, d, s, bx, CU_TENSOR_MAP_L2_PROMOTION_NONE);
    }
    {
        const cuuint64_t d[3] = {64, (cuuint64_t)NB * HKV * SK, 2}, s[2] = {DH * 2, 128};
        const cuuint32_t bx[3] = {64, 128, 2};
        encode(fn, &tk, d_in[1], 3, d, s, bx, CU_TENSOR_MAP_L2_PROMOTION_L2_256B);
        encode(fn, &tv, d_in[2], 3, d, s, bx, CU_TENSOR_MAP_L2_PROMOTION_L2_256B);
    }
    {
        const cuuint64_t d[3] = {64, DM, HQ * DH / 64}, s[2] = {HQ * DH * 2, 128};
        const cuuint32_t bx[3] = {64, 64, 4};
        encode(fn, &twq, d_in[3], 3, d, s, bx, CU_TENSOR_MAP_L2_PROMOTION_NONE);
    }
    {
        const cuuint64_t d[2] = {DM, HQ * DH}, s[1] = {DM * 2};
        const cuuint32_t bx[2] = {64, 256};
        encode(fn, &two, d_in[4], 2, d, s, bx, CU_TENSOR_MAP_L2_PROMOTION_L2_128B);
    }
    const int clear_in_kernel = 2 * pairs >= NCTA;
    if (!clear_in_kernel) cudaMemsetAsync(d_out, 0, (size_t)NB * SQ * DM * 2, cudaStreamPerThread);
    const int grid = (XTRA && 2 * pairs >= NCTA + 4) ? NCTA + 4 : NCTA;
    gqa_fused_kernel<<<grid, NTHREADS, SMEM_BYTES, cudaStreamPerThread>>>(
        tx, twq, tk, tv, two, tout, (__nv_bfloat16*)d_out, (const uint8_t*)d_in[0], (const uint8_t*)d_in[3],
        (const uint8_t*)d_in[1], (const uint8_t*)d_in[2], clear_in_kernel, map_mode);
}
```
